```python
import torch

def _softmax(x, axis=-1):
    return torch.softmax(x, dim=axis)
def _gelu(x):
    return torch.nn.functional.gelu(x, approximate="tanh")
def _silu(x):
    return torch.nn.functional.silu(x)
def _sigmoid(x):
    return torch.sigmoid(x)
def _layernorm(x, axis=-1, eps=1e-5):
    m = x.mean(dim=axis, keepdim=True)
    v = x.var(dim=axis, keepdim=True, unbiased=False)
    return (x - m) / torch.sqrt(v + eps)
def _scatter_add(tgt, idx, src, axis=0):
    return tgt.clone().index_add_(axis, idx, src)
def _segment_sum(src, seg, n):
    out = torch.zeros((n,) + src.shape[1:], dtype=src.dtype)
    return out.index_add_(0, seg, src)
def _pad(x, pw):
    flat = tuple(v for pair in reversed(pw) for v in pair)
    return torch.nn.functional.pad(x, flat)

kernel_name = 'sequential_preLN__mha_block__moe_arch_mod__prompt'

def setup_inputs():

    _w = (lambda a: (lambda t: t.to(torch.bfloat16) if t.is_floating_point() else t)(torch.as_tensor(a)))
    def _A_setup():
        B, S, D, H = 1, 2048, 640, 32
        return {
            "x": _w((lambda *s: torch.randn(*s, dtype=torch.bfloat16) * 0.05)(B, S, D)),
            "wqkv": _w((lambda *s: torch.randn(*s, dtype=torch.bfloat16) * 0.05)(D, 3 * D)),
            "wo": _w((lambda *s: torch.randn(*s, dtype=torch.bfloat16) * 0.05)(D, D)),
        }
    _A_in = _A_setup()

    def _B_setup():
        B, S, D, F, C = 1, 2048, 640, 1536, 2
        return {
            "x": _w((lambda *s: torch.randn(*s, dtype=torch.bfloat16) * 0.05)(B, S, D)),
            "w_r": _w((lambda *s: torch.randn(*s, dtype=torch.bfloat16) * 0.05)(D)),
            "w_gate": _w((lambda *s: torch.randn(*s, dtype=torch.bfloat16) * 0.05)(D, F)),
            "w_up": _w((lambda *s: torch.randn(*s, dtype=torch.bfloat16) * 0.05)(D, F)),
            "w_down": _w((lambda *s: torch.randn(*s, dtype=torch.bfloat16) * 0.05)(F, D)),
        }
    _B_in = _B_setup()

    return {
        "A_x": _A_in["x"],
        "A_wqkv": _A_in["wqkv"],
        "A_wo": _A_in["wo"],
        "B_x": _B_in["x"],
        "B_w_r": _B_in["w_r"],
        "B_w_gate": _B_in["w_gate"],
        "B_w_up": _B_in["w_up"],
        "B_w_down": _B_in["w_down"],
    }

def reference(A_x, A_wqkv, A_wo, B_x, B_w_r, B_w_gate, B_w_up, B_w_down):
    def _A_ref(x, wqkv, wo):
        B, S, D = x.shape
        H = 32
        Dh = D // H
        qkv = (lambda x, *d: x.permute(*d))((x @ wqkv).reshape(B, S, 3, H, Dh), 2, 0, 3, 1, 4)
        q, k, v = qkv[0], qkv[1], qkv[2]
        scores = torch.einsum("bhqd,bhkd->bhqk", q, k) * (Dh ** -0.5)
        p = _softmax(scores, axis=-1)
        o = torch.einsum("bhqk,bhkd->bhqd", p, v)
        return (lambda x, *d: x.permute(*d))(o, 0, 2, 1, 3).reshape(B, S, D) @ wo

    def _B_ref(x, w_r, w_gate, w_up, w_down):
        B, S, D = x.shape
        C = 2
        r = x @ w_r
        idx = torch.argsort(-r, axis=-1)[:, :C]
        idx_e = (lambda x, n, axis: torch.repeat_interleave(x, n, dim=axis))(idx.reshape(B, C, 1), D, axis=2)
        x_sel = (lambda x, i, axis: torch.take_along_dim(x, i, dim=axis))(x, idx_e, axis=1)
        g = _silu(x_sel @ w_gate)
        u = x_sel @ w_up
        y = (g * u) @ w_down
        r_sel = _sigmoid((lambda x, i, axis: torch.take_along_dim(x, i, dim=axis))(r, idx, axis=1))
        y = y * r_sel.reshape(B, C, 1)
        b_off = (torch.arange(B) * S).reshape(B, 1)
        flat_idx = (idx + b_off).reshape(B * C)
        zero = (x * 0.0).reshape(B * S, D)
        upd = _scatter_add(zero, flat_idx, y.reshape(B * C, D), axis=0)
        return x + upd.reshape(B, S, D)

    x = A_x
    h = x + _A_ref(_layernorm(x, axis=-1), A_wqkv, A_wo)
    h2 = h + _B_ref(_layernorm(h, axis=-1), B_w_r, B_w_gate, B_w_up, B_w_down)
    return h2
```

```cpp
#include <cuda_runtime.h>
#include <cuda_bf16.h>
#include <cuda.h>
#include <stdint.h>

typedef __nv_bfloat16 bf16;

constexpr int S_LEN = 2048, DM = 640, NHEAD = 32, DFF = 1536;
constexpr int UNIT_BYTES = 98304;
constexpr uint32_t POLY_MASK = 0xB5;
constexpr float QSCALE = 0.22360679774997896f * 1.4426950408889634f;

__device__ __align__(1024) uint8_t g_img[96 * UNIT_BYTES];
__device__ __align__(16) float g_csum[10 * 1920];
__device__ __align__(16) float2 g_rstat[5 * S_LEN];
__device__ unsigned g_cntN[8], g_cntM[16], g_cnt4;
__device__ __align__(16) float g_kmax[NHEAD * 128];
__device__ __align__(1024) bf16 g_O[S_LEN * DM];
__device__ __align__(1024) uint8_t g_wo[8 * 102400];
__device__ __align__(16) bf16 g_h[S_LEN * DM];
__device__ __align__(16) float g_st[3 * S_LEN];
__device__ __align__(16) float g_y[2 * DM];

__device__ __forceinline__ uint32_t smem_u32(const void* p) { return (uint32_t)__cvta_generic_to_shared(p); }
__device__ __forceinline__ uint64_t mkdesc(uint32_t addr, uint32_t lbo, uint32_t sbo, uint32_t swz) {
    return (uint64_t)((addr & 0x3FFFF) >> 4) | ((uint64_t)(lbo >> 4) << 16) | ((uint64_t)(sbo >> 4) << 32) | ((uint64_t)swz << 62);
}
__device__ __forceinline__ void wg_fence() { asm volatile("wgmma.fence.sync.aligned;" ::: "memory"); }
__device__ __forceinline__ void wg_commit() { asm volatile("wgmma.commit_group.sync.aligned;" ::: "memory"); }
template<int N> __device__ __forceinline__ void wg_wait() { asm volatile("wgmma.wait_group.sync.aligned %0;" :: "n"(N) : "memory"); }
__device__ __forceinline__ void mbar_init(uint32_t bar, uint32_t cnt) { asm volatile("mbarrier.init.shared::cta.b64 [%0], %1;" :: "r"(bar), "r"(cnt) : "memory"); }
__device__ __forceinline__ void mbar_expect_tx(uint32_t bar, uint32_t bytes) { asm volatile("mbarrier.arrive.expect_tx.shared::cta.b64 _, [%0], %1;" :: "r"(bar), "r"(bytes) : "memory"); }
__device__ __forceinline__ void mbar_arrive(uint32_t bar) { asm volatile("mbarrier.arrive.shared::cta.b64 _, [%0];" :: "r"(bar) : "memory"); }
__device__ __forceinline__ void mbar_arrive_cluster(uint32_t bar, uint32_t cta) {
    asm volatile("{.reg .b32 ra; mapa.shared::cluster.u32 ra, %0, %1; mbarrier.arrive.release.cluster.shared::cluster.b64 _, [ra];}" :: "r"(bar), "r"(cta) : "memory");
}
__device__ __forceinline__ bool mbar_try(uint32_t bar, uint32_t parity) {
    uint32_t ok;
    asm volatile("{.reg .pred p; mbarrier.try_wait.parity.shared::cta.b64 p, [%1], %2; selp.u32 %0, 1, 0, p;}" : "=r"(ok) : "r"(bar), "r"(parity) : "memory");
    return ok;
}
__device__ __forceinline__ bool mbar_try_cluster(uint32_t bar, uint32_t parity) {
    uint32_t ok;
    asm volatile("{.reg .pred p; mbarrier.try_wait.parity.acquire.cluster.shared::cta.b64 p, [%1], %2; selp.u32 %0, 1, 0, p;}" : "=r"(ok) : "r"(bar), "r"(parity) : "memory");
    return ok;
}
__device__ __forceinline__ void mbar_wait(uint32_t bar, uint32_t parity) {
    if (mbar_try(bar, parity)) return;
    uint32_t n = 0;
    while (!mbar_try(bar, parity)) { if (++n > (1u << 22)) __trap(); }
}
__device__ __forceinline__ void mbar_wait_cluster(uint32_t bar, uint32_t parity) {
    uint32_t n = 0;
    while (!mbar_try_cluster(bar, parity)) { if (++n > (1u << 22)) __trap(); }
}
__device__ __forceinline__ void fence_mbar_init() { asm volatile("fence.mbarrier_init.release.cluster;" ::: "memory"); }
__device__ __forceinline__ void fence_proxy_async() { asm volatile("fence.proxy.async.shared::cta;" ::: "memory"); }
__device__ __forceinline__ void cluster_arrive() { asm volatile("barrier.cluster.arrive.release.aligned;" ::: "memory"); }
__device__ __forceinline__ void cluster_wait() { asm volatile("barrier.cluster.wait.acquire.aligned;" ::: "memory"); }
__device__ __forceinline__ void bar_sync(int id, int n) { asm volatile("bar.sync %0, %1;" :: "r"(id), "r"(n) : "memory"); }
__device__ __forceinline__ void pdl_wait() { asm volatile("griddepcontrol.wait;" ::: "memory"); }
__device__ __forceinline__ void pdl_launch() { asm volatile("griddepcontrol.launch_dependents;" ::: "memory"); }
__device__ __forceinline__ void bulk_g2s(uint32_t dst, const void* src, uint32_t bytes, uint32_t bar) {
    asm volatile("cp.async.bulk.shared::cluster.global.mbarrier::complete_tx::bytes [%0], [%1], %2, [%3];" :: "r"(dst), "l"(src), "r"(bytes), "r"(bar) : "memory");
}
__device__ __forceinline__ void bulk_s2g(void* dst, uint32_t src, uint32_t bytes) {
    asm volatile("cp.async.bulk.global.shared::cta.bulk_group [%0], [%1], %2;" :: "l"(dst), "r"(src), "r"(bytes) : "memory");
}
__device__ __forceinline__ void tma2d(uint32_t dst, const CUtensorMap* tm, int x, int y, uint32_t bar) {
    asm volatile("cp.async.bulk.tensor.2d.shared::cluster.global.mbarrier::complete_tx::bytes [%0], [%1, {%2, %3}], [%4];"
        :: "r"(dst), "l"(tm), "r"(x), "r"(y), "r"(bar) : "memory");
}
__device__ __forceinline__ void tma2d_mc(uint32_t dst, const CUtensorMap* tm, int x, int y, uint32_t bar, uint16_t mask) {
    asm volatile("cp.async.bulk.tensor.2d.shared::cluster.global.mbarrier::complete_tx::bytes.multicast::cluster [%0], [%1, {%2, %3}], [%4], %5;"
        :: "r"(dst), "l"(tm), "r"(x), "r"(y), "r"(bar), "h"(mask) : "memory");
}
__device__ __forceinline__ void prefetch_tm(const CUtensorMap* tm) { asm volatile("prefetch.tensormap [%0];" :: "l"(tm) : "memory"); }
template<int N> __device__ __forceinline__ void fence_f(float (&d)[N]) {
    #pragma unroll
    for (int i = 0; i < N; i++) asm volatile("" : "+f"(d[i]) :: "memory");
}
template<int N> __device__ __forceinline__ void fence_u(uint32_t (&d)[N]) {
    #pragma unroll
    for (int i = 0; i < N; i++) asm volatile("" : "+r"(d[i]) :: "memory");
}
__device__ __forceinline__ float ex2f(float x) { float y; asm("ex2.approx.ftz.f32 %0, %1;" : "=f"(y) : "f"(x)); return y; }
__device__ __forceinline__ uint32_t pack_bf16(float lo, float hi) { uint32_t r; asm("cvt.rn.bf16x2.f32 %0, %1, %2;" : "=r"(r) : "f"(hi), "f"(lo)); return r; }
__device__ __forceinline__ float bf_lo(uint32_t u) { return __uint_as_float(u << 16); }
__device__ __forceinline__ float bf_hi(uint32_t u) { return __uint_as_float(u & 0xffff0000u); }
__device__ __forceinline__ float bf_round(float x) { return __bfloat162float(__float2bfloat16_rn(x)); }
__device__ __forceinline__ unsigned ld_acquire(const unsigned* p) { unsigned v; asm volatile("ld.acquire.gpu.global.u32 %0, [%1];" : "=r"(v) : "l"(p) : "memory"); return v; }
__device__ __forceinline__ void red_release(unsigned* p, unsigned v) { asm volatile("red.release.gpu.global.add.u32 [%0], %1;" :: "l"(p), "r"(v) : "memory"); }
__device__ __forceinline__ void spin_until(const unsigned* p, unsigned target) {
    uint32_t n = 0;
    while (ld_acquire(p) < target) { if (++n > (1u << 22)) __trap(); }
}
__device__ __forceinline__ uint4 lds128(uint32_t a) { uint4 v; asm volatile("ld.shared.v4.u32 {%0,%1,%2,%3}, [%4];" : "=r"(v.x), "=r"(v.y), "=r"(v.z), "=r"(v.w) : "r"(a)); return v; }
__device__ __forceinline__ void sts32(uint32_t a, uint32_t v) { asm volatile("st.shared.u32 [%0], %1;" :: "r"(a), "r"(v) : "memory"); }
__device__ __forceinline__ void sts64(uint32_t a, uint32_t v0, uint32_t v1) { asm volatile("st.shared.v2.u32 [%0], {%1,%2};" :: "r"(a), "r"(v0), "r"(v1) : "memory"); }

__device__ __forceinline__ void wg_ss240(float (&d)[120], uint64_t da, uint64_t db, int sc) {
    asm volatile("{.reg .pred p; setp.ne.b32 p, %122, 0;\n"
        "wgmma.mma_async.sync.aligned.m64n240k16.f32.bf16.bf16 {%0,%1,%2,%3,%4,%5,%6,%7,%8,%9,%10,%11,%12,%13,%14,%15,%16,%17,%18,%19,%20,%21,%22,%23,%24,%25,%26,%27,%28,%29,%30,%31,%32,%33,%34,%35,%36,%37,%38,%39,%40,%41,%42,%43,%44,%45,%46,%47,%48,%49,%50,%51,%52,%53,%54,%55,%56,%57,%58,%59,%60,%61,%62,%63,%64,%65,%66,%67,%68,%69,%70,%71,%72,%73,%74,%75,%76,%77,%78,%79,%80,%81,%82,%83,%84,%85,%86,%87,%88,%89,%90,%91,%92,%93,%94,%95,%96,%97,%98,%99,%100,%101,%102,%103,%104,%105,%106,%107,%108,%109,%110,%111,%112,%113,%114,%115,%116,%117,%118,%119}, %120, %121, p, 1, 1, 0, 1;}"
        : "+f"(d[0]),"+f"(d[1]),"+f"(d[2]),"+f"(d[3]),"+f"(d[4]),"+f"(d[5]),"+f"(d[6]),"+f"(d[7]),"+f"(d[8]),"+f"(d[9]),"+f"(d[10]),"+f"(d[11]),"+f"(d[12]),"+f"(d[13]),"+f"(d[14]),"+f"(d[15]),"+f"(d[16]),"+f"(d[17]),"+f"(d[18]),"+f"(d[19]),"+f"(d[20]),"+f"(d[21]),"+f"(d[22]),"+f"(d[23]),"+f"(d[24]),"+f"(d[25]),"+f"(d[26]),"+f"(d[27]),"+f"(d[28]),"+f"(d[29]),"+f"(d[30]),"+f"(d[31]),"+f"(d[32]),"+f"(d[33]),"+f"(d[34]),"+f"(d[35]),"+f"(d[36]),"+f"(d[37]),"+f"(d[38]),"+f"(d[39]),"+f"(d[40]),"+f"(d[41]),"+f"(d[42]),"+f"(d[43]),"+f"(d[44]),"+f"(d[45]),"+f"(d[46]),"+f"(d[47]),"+f"(d[48]),"+f"(d[49]),"+f"(d[50]),"+f"(d[51]),"+f"(d[52]),"+f"(d[53]),"+f"(d[54]),"+f"(d[55]),"+f"(d[56]),"+f"(d[57]),"+f"(d[58]),"+f"(d[59]),"+f"(d[60]),"+f"(d[61]),"+f"(d[62]),"+f"(d[63]),"+f"(d[64]),"+f"(d[65]),"+f"(d[66]),"+f"(d[67]),"+f"(d[68]),"+f"(d[69]),"+f"(d[70]),"+f"(d[71]),"+f"(d[72]),"+f"(d[73]),"+f"(d[74]),"+f"(d[75]),"+f"(d[76]),"+f"(d[77]),"+f"(d[78]),"+f"(d[79]),"+f"(d[80]),"+f"(d[81]),"+f"(d[82]),"+f"(d[83]),"+f"(d[84]),"+f"(d[85]),"+f"(d[86]),"+f"(d[87]),"+f"(d[88]),"+f"(d[89]),"+f"(d[90]),"+f"(d[91]),"+f"(d[92]),"+f"(d[93]),"+f"(d[94]),"+f"(d[95]),"+f"(d[96]),"+f"(d[97]),"+f"(d[98]),"+f"(d[99]),"+f"(d[100]),"+f"(d[101]),"+f"(d[102]),"+f"(d[103]),"+f"(d[104]),"+f"(d[105]),"+f"(d[106]),"+f"(d[107]),"+f"(d[108]),"+f"(d[109]),"+f"(d[110]),"+f"(d[111]),"+f"(d[112]),"+f"(d[113]),"+f"(d[114]),"+f"(d[115]),"+f"(d[116]),"+f"(d[117]),"+f"(d[118]),"+f"(d[119])
        : "l"(da), "l"(db), "r"(sc));
}
__device__ __forceinline__ void wg_ss80(float (&d)[40], uint64_t da, uint64_t db, int sc) {
    asm volatile("{.reg .pred p; setp.ne.b32 p, %42, 0;\n"
        "wgmma.mma_async.sync.aligned.m64n80k16.f32.bf16.bf16 {%0,%1,%2,%3,%4,%5,%6,%7,%8,%9,%10,%11,%12,%13,%14,%15,%16,%17,%18,%19,%20,%21,%22,%23,%24,%25,%26,%27,%28,%29,%30,%31,%32,%33,%34,%35,%36,%37,%38,%39}, %40, %41, p, 1, 1, 0, 1;}"
        : "+f"(d[0]),"+f"(d[1]),"+f"(d[2]),"+f"(d[3]),"+f"(d[4]),"+f"(d[5]),"+f"(d[6]),"+f"(d[7]),"+f"(d[8]),"+f"(d[9]),"+f"(d[10]),"+f"(d[11]),"+f"(d[12]),"+f"(d[13]),"+f"(d[14]),"+f"(d[15]),"+f"(d[16]),"+f"(d[17]),"+f"(d[18]),"+f"(d[19]),"+f"(d[20]),"+f"(d[21]),"+f"(d[22]),"+f"(d[23]),"+f"(d[24]),"+f"(d[25]),"+f"(d[26]),"+f"(d[27]),"+f"(d[28]),"+f"(d[29]),"+f"(d[30]),"+f"(d[31]),"+f"(d[32]),"+f"(d[33]),"+f"(d[34]),"+f"(d[35]),"+f"(d[36]),"+f"(d[37]),"+f"(d[38]),"+f"(d[39])
        : "l"(da), "l"(db), "r"(sc));
}
template<int SC> __device__ __forceinline__ void wg_rs64(float (&d)[32], uint32_t a0, uint32_t a1, uint32_t a2, uint32_t a3, uint64_t db) {
    asm volatile("wgmma.mma_async.sync.aligned.m64n64k16.f32.bf16.bf16 {%0,%1,%2,%3,%4,%5,%6,%7,%8,%9,%10,%11,%12,%13,%14,%15,%16,%17,%18,%19,%20,%21,%22,%23,%24,%25,%26,%27,%28,%29,%30,%31}, {%32,%33,%34,%35}, %36, %37, 1, 1, 0;"
        : "+f"(d[0]),"+f"(d[1]),"+f"(d[2]),"+f"(d[3]),"+f"(d[4]),"+f"(d[5]),"+f"(d[6]),"+f"(d[7]),"+f"(d[8]),"+f"(d[9]),"+f"(d[10]),"+f"(d[11]),"+f"(d[12]),"+f"(d[13]),"+f"(d[14]),"+f"(d[15]),"+f"(d[16]),"+f"(d[17]),"+f"(d[18]),"+f"(d[19]),"+f"(d[20]),"+f"(d[21]),"+f"(d[22]),"+f"(d[23]),"+f"(d[24]),"+f"(d[25]),"+f"(d[26]),"+f"(d[27]),"+f"(d[28]),"+f"(d[29]),"+f"(d[30]),"+f"(d[31])
        : "r"(a0), "r"(a1), "r"(a2), "r"(a3), "l"(db), "n"(SC));
}
template<int SC> __device__ __forceinline__ void wg_pv24(float (&d)[12], uint32_t a0, uint32_t a1, uint32_t a2, uint32_t a3, uint64_t db) {
    asm volatile("wgmma.mma_async.sync.aligned.m64n24k16.f32.bf16.bf16 {%0,%1,%2,%3,%4,%5,%6,%7,%8,%9,%10,%11}, {%12,%13,%14,%15}, %16, %17, 1, 1, 1;"
        : "+f"(d[0]),"+f"(d[1]),"+f"(d[2]),"+f"(d[3]),"+f"(d[4]),"+f"(d[5]),"+f"(d[6]),"+f"(d[7]),"+f"(d[8]),"+f"(d[9]),"+f"(d[10]),"+f"(d[11])
        : "r"(a0), "r"(a1), "r"(a2), "r"(a3), "l"(db), "n"(SC));
}

constexpr int P1_STAGE = 49152;
constexpr int P1_MISC = 4 * P1_STAGE;
constexpr int P1_SMEM = P1_MISC + 4096 + 1024;
constexpr int P1_THREADS = 384;

__global__ void __launch_bounds__(P1_THREADS, 1)
p1_qkv(const __grid_constant__ CUtensorMap tmX, const __grid_constant__ CUtensorMap tmW, const bf16* __restrict__ wo) {
    extern __shared__ uint8_t smem_raw[];
    const uint32_t sb = (smem_u32(smem_raw) + 1023) & ~1023u;
    const int tid = threadIdx.x;
    const int warp = __shfl_sync(0xffffffff, tid >> 5, 0), lane = tid & 31;
    pdl_launch();
    if (blockIdx.x >= 128) {
        const int base = (blockIdx.x - 128) * 12800;
        #pragma unroll 1
        for (int q0 = tid; q0 < 12800; q0 += P1_THREADS * 8) {
            uint4 v[8];
            #pragma unroll
            for (int u = 0; u < 8; u++) {
                int q = q0 + u * P1_THREADS;
                if (q < 12800) { int qq = base + q; v[u] = __ldg((const uint4*)(wo + (qq / 80) * DM + (qq % 80) * 8)); }
            }
            #pragma unroll
            for (int u = 0; u < 8; u++) {
                int q = q0 + u * P1_THREADS;
                if (q < 12800) {
                    int qq = base + q, k = qq / 80, nc = qq % 80;
                    *(uint4*)(g_wo + (nc / 10) * 102400 + (k >> 3) * 1280 + (nc % 10) * 128 + (k & 7) * 16) = v[u];
                }
            }
        }
        return;
    }
    const int rank = blockIdx.x & 1, pr = blockIdx.x >> 1;
    const int j = pr & 7, mp = pr >> 3, mt = 2 * mp + rank;
    const int s0 = (2 * mp + 2 * j) % 10;
    const uint32_t bar_full = sb + P1_MISC, bar_empty = bar_full + 32, bar_stat = bar_full + 64;
    const uint32_t s_mu = sb + P1_MISC + 128, s_rs = s_mu + 512, s_cs = s_rs + 512;
    if (tid == 0) {
        for (int i = 0; i < 4; i++) { mbar_init(bar_full + 8 * i, 1); mbar_init(bar_empty + 8 * i, 4); }
        mbar_init(bar_stat, 2);
        fence_mbar_init();
    }
    __syncthreads();
    cluster_arrive(); cluster_wait();

    if (warp < 4) {
        auto issue = [&](int it) {
            const int s = it & 3;
            int c = s0 + it; if (c >= 10) c -= 10;
            const uint32_t st = sb + s * P1_STAGE;
            mbar_expect_tx(bar_full + 8 * s, P1_STAGE);
            tma2d(st, &tmX, 64 * c, 128 * mt, bar_full + 8 * s);
            tma2d_mc(st + 16384 + (2 * rank) * 8192, &tmW, 240 * j + 128 * rank, 64 * c, bar_full + 8 * s, 3);
            tma2d_mc(st + 16384 + (2 * rank + 1) * 8192, &tmW, 240 * j + 128 * rank + 64, 64 * c, bar_full + 8 * s, 3);
        };
        if (tid == 0) { for (int it = 0; it < 4; it++) issue(it); }
        __syncwarp();
        const int r = tid, w = warp;
        const bool do_rows = j < 5, do_cols = mp < 5;
        if (do_rows || do_cols) { mbar_wait(bar_full, 0); mbar_wait(bar_full + 8, 0); }
        if (do_rows) {
            float sx = 0.f, sq = 0.f;
            #pragma unroll
            for (int st = 0; st < 2; st++) {
                #pragma unroll
                for (int c = 0; c < 8; c++) {
                    uint4 v = lds128(sb + st * P1_STAGE + r * 128 + ((c ^ (r & 7)) << 4));
                    uint32_t u[4] = {v.x, v.y, v.z, v.w};
                    #pragma unroll
                    for (int e = 0; e < 4; e++) { float a = bf_lo(u[e]), b = bf_hi(u[e]); sx += a + b; sq = fmaf(a, a, sq); sq = fmaf(b, b, sq); }
                }
            }
            g_rstat[(s0 >> 1) * S_LEN + 128 * mt + r] = make_float2(sx, sq);
        }
        if (do_cols) {
            float a[8];
            #pragma unroll
            for (int e = 0; e < 8; e++) a[e] = 0.f;
            const int kq = lane >> 3, c8 = lane & 7;
            const uint32_t bt = sb + rank * P1_STAGE + 16384 + w * 8192;
            #pragma unroll
            for (int x = 0; x < 16; x++) {
                const int k = 16 * kq + x;
                uint4 v = lds128(bt + k * 128 + ((c8 ^ (k & 7)) << 4));
                a[0] += bf_lo(v.x); a[1] += bf_hi(v.x); a[2] += bf_lo(v.y); a[3] += bf_hi(v.y);
                a[4] += bf_lo(v.z); a[5] += bf_hi(v.z); a[6] += bf_lo(v.w); a[7] += bf_hi(v.w);
            }
            #pragma unroll
            for (int e = 0; e < 8; e++) { a[e] += __shfl_xor_sync(0xffffffff, a[e], 8); a[e] += __shfl_xor_sync(0xffffffff, a[e], 16); }
            int c = s0 + rank; if (c >= 10) c -= 10;
            const int n = 64 * w + 8 * c8;
            if (kq == 0 && n < 240) {
                float4* dst = (float4*)(g_csum + c * 1920 + 240 * j + n);
                dst[0] = make_float4(a[0], a[1], a[2], a[3]); dst[1] = make_float4(a[4], a[5], a[6], a[7]);
            }
        }
        bar_sync(1, 128);
        if (r == 32) {
            __threadfence();
            if (do_rows) red_release(&g_cntM[mt], 1);
            if (do_cols) red_release(&g_cntN[j], 1);
            spin_until(&g_cntM[mt], 5);
            spin_until(&g_cntN[j], 10);
        }
        if (r == 0) {
            mbar_arrive_cluster(bar_stat, 0); mbar_arrive_cluster(bar_stat, 1);
            mbar_wait_cluster(bar_stat, 0);
            #pragma unroll 1
            for (int it = 4; it < 10; it++) {
                mbar_wait_cluster(bar_empty + 8 * (it & 3), ((it >> 2) - 1) & 1);
                issue(it);
            }
        }
        __syncwarp();
        bar_sync(1, 128);
        {
            float sx = 0.f, sq = 0.f;
            #pragma unroll
            for (int p = 0; p < 5; p++) { float2 v = __ldcg(&g_rstat[p * S_LEN + 128 * mt + r]); sx += v.x; sq += v.y; }
            const float mu = sx * (1.f / DM);
            const float var = fmaxf(sq * (1.f / DM) - mu * mu, 0.f);
            asm volatile("st.shared.f32 [%0], %1;" :: "r"(s_mu + 4 * r), "f"(mu) : "memory");
            asm volatile("st.shared.f32 [%0], %1;" :: "r"(s_rs + 4 * r), "f"(1.f / sqrtf(var + 1e-5f)) : "memory");
            #pragma unroll
            for (int h = 0; h < 2; h++) {
                const int n = r + 128 * h;
                if (n < 240) {
                    float cs = 0.f;
                    #pragma unroll
                    for (int c = 0; c < 10; c++) cs += __ldcg(&g_csum[c * 1920 + 240 * j + n]);
                    asm volatile("st.shared.f32 [%0], %1;" :: "r"(s_cs + 4 * n), "f"(cs) : "memory");
                }
            }
        }
        bar_sync(2, 384);
        {
            const bool poly = (POLY_MASK >> ((r >> 3) & 7)) & 1;
            #pragma unroll
            for (int ul = 0; ul < 12; ul++) {
                const int u = 12 * j + ul;
                uint32_t v0 = 0, v1 = 0;
                if (u >= 64) v0 = 0x00003F80u;
                else if (u >= 32 && poly) { v0 = 0x42FE4780u; v1 = 0x00003B80u; }
                sts64(sb + ul * 6144 + (r >> 3) * 384 + 256 + (r & 7) * 16 + 8, v0, v1);
            }
        }
        fence_proxy_async();
        bar_sync(3, 384);
        if (r < 12) {
            bulk_s2g(g_img + (size_t)(12 * j + r) * UNIT_BYTES + mt * 6144, sb + r * 6144, 6144);
            asm volatile("cp.async.bulk.commit_group;" ::: "memory");
            asm volatile("cp.async.bulk.wait_group 0;" ::: "memory");
        }
        __syncwarp();
        cluster_arrive(); cluster_wait();
    } else {
        const int wg = (warp >> 2) - 1, wq = warp & 3, g = lane >> 2, t = lane & 3;
        float acc[120];
        #pragma unroll 1
        for (int it = 0; it < 10; it++) {
            const int s = it & 3;
            mbar_wait(bar_full + 8 * s, (it >> 2) & 1);
            const uint32_t st = sb + s * P1_STAGE;
            const uint64_t da = mkdesc(st + wg * 8192, 16, 1024, 1), db = mkdesc(st + 16384, 8192, 1024, 1);
            wg_fence();
            #pragma unroll
            for (int kk = 0; kk < 4; kk++) wg_ss240(acc, da + kk * 2, db + kk * 128, (it | kk) != 0);
            wg_commit();
            if (it >= 1) {
                wg_wait<1>();
                if (it <= 6 && (tid & 127) == 0) { const uint32_t e = bar_empty + 8 * ((it - 1) & 3); mbar_arrive_cluster(e, 0); mbar_arrive_cluster(e, 1); }
            }
        }
        wg_wait<0>();
        fence_f(acc);
        bar_sync(2, 384);
        const int r0 = 64 * wg + 16 * wq + g;
        float mu0, mu1, rs0, rs1;
        asm volatile("ld.shared.f32 %0, [%1];" : "=f"(mu0) : "r"(s_mu + 4 * r0));
        asm volatile("ld.shared.f32 %0, [%1];" : "=f"(mu1) : "r"(s_mu + 4 * r0 + 32));
        asm volatile("ld.shared.f32 %0, [%1];" : "=f"(rs0) : "r"(s_rs + 4 * r0));
        asm volatile("ld.shared.f32 %0, [%1];" : "=f"(rs1) : "r"(s_rs + 4 * r0 + 32));
        const int nq = min(max((640 - 240 * j) / 8, 0), 30);
        const bool has_k = (j >= 2 && j <= 5);
        const int th = t >> 1;
        const uint32_t base = sb + (8 * wg + 2 * wq) * 384 + g * 16 + (t & 1) * 4;
        const uint32_t b8 = base + th * 8, b120 = base + th * 120, b5888 = base + th * 5888;
        float n0 = 0.f, n1 = 0.f;
        #pragma unroll
        for (int b = 0; b < 30; b++) {
            float c0, c1;
            asm volatile("ld.shared.v2.f32 {%0,%1}, [%2];" : "=f"(c0), "=f"(c1) : "r"(s_cs + 4 * (8 * b + 2 * t)));
            const float f0 = (b < nq) ? rs0 * QSCALE : rs0, f1 = (b < nq) ? rs1 * QSCALE : rs1;
            const float v0 = (acc[4 * b] - mu0 * c0) * f0, v1 = (acc[4 * b + 1] - mu0 * c1) * f0;
            const float v2 = (acc[4 * b + 2] - mu1 * c0) * f1, v3 = (acc[4 * b + 3] - mu1 * c1) * f1;
            const int q = 2 * b, dq = q % 5;
            const uint32_t offA = (q / 5) * 6144 + (dq / 2) * 128 + (dq % 2) * 8;
            const uint32_t ad = ((dq == 4) ? b5888 : ((dq & 1) ? b120 : b8)) + offA;
            sts32(ad, pack_bf16(v0, v1));
            sts32(ad + 384, pack_bf16(v2, v3));
            if (has_k) {
                const float e0 = fmaf(v0, v0, v1 * v1), e1 = fmaf(v2, v2, v3 * v3);
                float nx0 = 0.f, nx1 = 0.f;
                if (dq == 4) { n0 += th ? 0.f : e0; n1 += th ? 0.f : e1; nx0 = th ? e0 : 0.f; nx1 = th ? e1 : 0.f; }
                else { n0 += e0; n1 += e1; }
                if (dq == 3 || dq == 4) {
                    float m0 = n0 + __shfl_xor_sync(0xffffffff, n0, 1), m1 = n1 + __shfl_xor_sync(0xffffffff, n1, 1);
                    m0 += __shfl_xor_sync(0xffffffff, m0, 2); m1 += __shfl_xor_sync(0xffffffff, m1, 2);
                    float m = fmaxf(m0, m1);
                    if (!(m0 == m0) || !(m1 == m1)) m = __int_as_float(0x7f800000);
                    m = fmaxf(m, __shfl_xor_sync(0xffffffff, m, 4)); m = fmaxf(m, __shfl_xor_sync(0xffffffff, m, 8)); m = fmaxf(m, __shfl_xor_sync(0xffffffff, m, 16));
                    const int u = 12 * j + q / 5;
                    if (lane == 0 && u >= 32 && u < 64) g_kmax[(u - 32) * 128 + mt * 8 + warp - 4] = m;
                    n0 = nx0; n1 = nx1;
                }
            }
        }
        fence_proxy_async();
        bar_sync(3, 384);
        __syncwarp();
        cluster_arrive(); cluster_wait();
    }
}

constexpr int P2_SMEM = 2 * UNIT_BYTES + 256 + 1024;
constexpr float SAFE_BOUND2 = 9800.f;

__device__ __forceinline__ uint32_t exp2_bf16x2(float t0, float t1) {
    uint32_t u, z, p, r;
    asm("prmt.b32 %0, %1, %2, 0x5410;" : "=r"(u) : "r"(__float_as_uint(t0)), "r"(__float_as_uint(t1)));
    asm("lop3.b32 %0, %1, 0x007F007F, 0x3F803F80, 0xEA;" : "=r"(z) : "r"(u));
    asm("fma.rn.bf16x2 %0, %1, %2, %3;" : "=r"(p) : "r"(z), "r"(0x3EAC3EACu), "r"(0xBC99BC99u));
    asm("fma.rn.bf16x2 %0, %1, %2, %3;" : "=r"(p) : "r"(p), "r"(z), "r"(0x3F303F30u));
    asm("lop3.b32 %0, %1, %2, 0xFF80FF80, 0xE4;" : "=r"(r) : "r"(u), "r"(p));
    return r;
}

template<bool FIRST>
__device__ __forceinline__ void attn_fast(float (&o)[12], const uint32_t (&q)[6], uint32_t zz, uint64_t dK0, uint64_t dK1, uint64_t dV, uint32_t bars) {
    float s[32]; uint32_t p[16];
    if (FIRST) mbar_wait(bars, 0);
    wg_fence();
    wg_rs64<0>(s, q[0], q[1], q[2], q[3], dK0);
    wg_rs64<1>(s, q[4], q[5], zz, zz, dK1);
    wg_commit();
    #pragma unroll 1
    for (int jj = 0; jj < 32; jj++) {
        wg_wait<0>(); fence_f(s); fence_f(o);
        #pragma unroll
        for (int b = 0; b < 8; b++) {
            if ((POLY_MASK >> b) & 1) { p[2 * b] = exp2_bf16x2(s[4 * b], s[4 * b + 1]); p[2 * b + 1] = exp2_bf16x2(s[4 * b + 2], s[4 * b + 3]); }
            else { p[2 * b] = pack_bf16(ex2f(s[4 * b]), ex2f(s[4 * b + 1])); p[2 * b + 1] = pack_bf16(ex2f(s[4 * b + 2]), ex2f(s[4 * b + 3])); }
        }
        const int jn = (jj + 1 < 32) ? jj + 1 : 0;
        if (FIRST && (jj & 1) && jj + 1 < 32) mbar_wait(bars + 8 * ((jj + 1) >> 1), 0);
        fence_u(p);
        wg_fence();
        wg_rs64<0>(s, q[0], q[1], q[2], q[3], dK0 + (uint64_t)(jn * 192));
        wg_rs64<1>(s, q[4], q[5], zz, zz, dK1 + (uint64_t)(jn * 192));
        #pragma unroll
        for (int k = 0; k < 4; k++) wg_pv24<1>(o, p[4 * k], p[4 * k + 1], p[4 * k + 2], p[4 * k + 3], dV + (uint64_t)(jj * 192 + k * 48));
        wg_commit();
    }
    wg_wait<0>(); fence_f(o); fence_f(s);
}

__device__ __forceinline__ void attn_safe(float (&o)[12], const uint32_t (&qin)[6], uint64_t dK0, uint64_t dK1, uint64_t dV, uint32_t bars, int t) {
    float s[32]; uint32_t p[16];
    uint32_t q4 = (t < 2) ? qin[4] : 0u, q5 = (t < 2) ? qin[5] : 0u;
    uint32_t zz = 0; asm volatile("" : "+r"(zz));
    float m0 = -INFINITY, m1 = -INFINITY;
    #pragma unroll 1
    for (int jj = 0; jj < 32; jj++) {
        mbar_wait(bars + 8 * (jj >> 1), 0);
        wg_fence();
        wg_rs64<0>(s, qin[0], qin[1], qin[2], qin[3], dK0 + (uint64_t)(jj * 192));
        wg_rs64<1>(s, q4, q5, zz, zz, dK1 + (uint64_t)(jj * 192));
        wg_commit();
        wg_wait<0>(); fence_f(s); fence_f(o);
        float a0 = m0, a1 = m1;
        #pragma unroll
        for (int b = 0; b < 8; b++) { a0 = fmaxf(a0, fmaxf(s[4 * b], s[4 * b + 1])); a1 = fmaxf(a1, fmaxf(s[4 * b + 2], s[4 * b + 3])); }
        a0 = fmaxf(a0, __shfl_xor_sync(0xffffffff, a0, 1)); a0 = fmaxf(a0, __shfl_xor_sync(0xffffffff, a0, 2));
        a1 = fmaxf(a1, __shfl_xor_sync(0xffffffff, a1, 1)); a1 = fmaxf(a1, __shfl_xor_sync(0xffffffff, a1, 2));
        const float c0 = (m0 == a0) ? 1.f : ex2f(m0 - a0), c1 = (m1 == a1) ? 1.f : ex2f(m1 - a1);
        m0 = a0; m1 = a1;
        #pragma unroll
        for (int b = 0; b < 3; b++) { o[4 * b] *= c0; o[4 * b + 1] *= c0; o[4 * b + 2] *= c1; o[4 * b + 3] *= c1; }
        #pragma unroll
        for (int b = 0; b < 8; b++) {
            p[2 * b] = pack_bf16(ex2f(s[4 * b] - m0), ex2f(s[4 * b + 1] - m0));
            p[2 * b + 1] = pack_bf16(ex2f(s[4 * b + 2] - m1), ex2f(s[4 * b + 3] - m1));
        }
        fence_u(p); fence_f(o);
        wg_fence();
        #pragma unroll
        for (int k = 0; k < 4; k++) wg_pv24<1>(o, p[4 * k], p[4 * k + 1], p[4 * k + 2], p[4 * k + 3], dV + (uint64_t)(jj * 192 + k * 48));
        wg_commit();
        wg_wait<0>(); fence_f(o);
    }
}

__global__ void __launch_bounds__(512, 1)
p2_attn(const bf16* __restrict__ wg_, const bf16* __restrict__ wu_, const bf16* __restrict__ wd_) {
    extern __shared__ uint8_t smem_raw[];
    const uint32_t sb = (smem_u32(smem_raw) + 1023) & ~1023u;
    const int tid = threadIdx.x;
    const int warp = __shfl_sync(0xffffffff, tid >> 5, 0), lane = tid & 31;
    if (blockIdx.x >= 128) {
        const int c = blockIdx.x - 128;
        if (tid < 90) {
            const int i = c * 90 + tid;
            const char* src = (const char*)((i < 120) ? wg_ : (i < 240) ? wu_ : wd_) + (i % 120) * 16384;
            asm volatile("cp.async.bulk.prefetch.L2.global [%0], %1;" :: "l"(src), "r"(16384) : "memory");
        }
        pdl_wait();
        pdl_launch();
        if (c == 0) {
            for (int i = tid; i < 3 * S_LEN; i += 512) g_st[i] = 0.f;
            for (int i = tid; i < 2 * DM; i += 512) g_y[i] = 0.f;
            if (tid < 8) g_cntN[tid] = 0;
            if (tid < 16) g_cntM[tid] = 0;
            if (tid == 0) g_cnt4 = 0;
        }
        return;
    }
    const uint32_t sK = sb, sV = sb + UNIT_BYTES, bars = sb + 2 * UNIT_BYTES;
    const int head = blockIdx.x >> 2, qq = blockIdx.x & 3;
    const int wg = warp >> 2, wq = warp & 3, g = lane >> 2, t = lane & 3;
    if (tid == 0) { for (int i = 0; i < 16; i++) mbar_init(bars + 8 * i, 1); fence_mbar_init(); }
    __syncthreads();
    pdl_wait();
    pdl_launch();
    if (tid == 0) {
        const uint8_t* gk = g_img + (size_t)(32 + head) * UNIT_BYTES;
        const uint8_t* gv = g_img + (size_t)(64 + head) * UNIT_BYTES;
        for (int c = 0; c < 16; c++) {
            mbar_expect_tx(bars + 8 * c, 12288);
            bulk_g2s(sK + c * 6144, gk + c * 6144, 6144, bars + 8 * c);
            bulk_g2s(sV + c * 6144, gv + c * 6144, 6144, bars + 8 * c);
        }
    }
    uint32_t qf[2][6];
    #pragma unroll
    for (int tl = 0; tl < 2; tl++) {
        const int row0 = qq * 512 + (tl * 4 + wg) * 64 + wq * 16;
        const uint8_t* qb = g_img + (size_t)head * UNIT_BYTES + (row0 >> 3) * 384 + g * 16 + t * 4;
        qf[tl][0] = __ldcg((const uint32_t*)(qb)); qf[tl][1] = __ldcg((const uint32_t*)(qb + 384));
        qf[tl][2] = __ldcg((const uint32_t*)(qb + 128)); qf[tl][3] = __ldcg((const uint32_t*)(qb + 384 + 128));
        qf[tl][4] = __ldcg((const uint32_t*)(qb + 256)); qf[tl][5] = __ldcg((const uint32_t*)(qb + 384 + 256));
    }
    float km;
    {
        float4 v = __ldcg((const float4*)(g_kmax + head * 128) + lane);
        km = fmaxf(fmaxf(v.x, v.y), fmaxf(v.z, v.w));
        #pragma unroll
        for (int o = 16; o; o >>= 1) km = fmaxf(km, __shfl_xor_sync(0xffffffff, km, o));
    }
    const uint64_t dK0 = mkdesc(sK, 128, 384, 0), dK1 = mkdesc(sK + 256, 0, 384, 0), dV = mkdesc(sV, 384, 128, 0);
    uint32_t zz = 0; asm volatile("" : "+r"(zz));
    #pragma unroll 1
    for (int tl = 0; tl < 2; tl++) {
        uint32_t q[6];
        #pragma unroll
        for (int i = 0; i < 6; i++) q[i] = tl ? qf[1][i] : qf[0][i];
        if (t >= 2) q[4] = q[5] = (t == 2 ? 0x3F803F80u : 0x00003F80u);
        fence_u(q);
        float n0 = 0.f, n1 = 0.f;
        {
            float a;
            a = bf_lo(q[0]); n0 = fmaf(a, a, n0); a = bf_hi(q[0]); n0 = fmaf(a, a, n0);
            a = bf_lo(q[2]); n0 = fmaf(a, a, n0); a = bf_hi(q[2]); n0 = fmaf(a, a, n0);
            a = bf_lo(q[1]); n1 = fmaf(a, a, n1); a = bf_hi(q[1]); n1 = fmaf(a, a, n1);
            a = bf_lo(q[3]); n1 = fmaf(a, a, n1); a = bf_hi(q[3]); n1 = fmaf(a, a, n1);
            if (t < 2) {
                a = bf_lo(q[4]); n0 = fmaf(a, a, n0); a = bf_hi(q[4]); n0 = fmaf(a, a, n0);
                a = bf_lo(q[5]); n1 = fmaf(a, a, n1); a = bf_hi(q[5]); n1 = fmaf(a, a, n1);
            }
            n0 += __shfl_xor_sync(0xffffffff, n0, 1); n0 += __shfl_xor_sync(0xffffffff, n0, 2);
            n1 += __shfl_xor_sync(0xffffffff, n1, 1); n1 += __shfl_xor_sync(0xffffffff, n1, 2);
        }
        const bool bad = !(n0 * km <= SAFE_BOUND2) || !(n1 * km <= SAFE_BOUND2);
        uint32_t unsafe;
        asm volatile("{.reg .pred p, r; setp.ne.u32 p, %1, 0; barrier.cta.red.or.aligned.pred r, %2, 128, p; selp.u32 %0, 1, 0, r;}"
            : "=r"(unsafe) : "r"((uint32_t)bad), "r"(1 + wg) : "memory");
        unsafe = __shfl_sync(0xffffffff, unsafe, 0);
        float o[12];
        #pragma unroll
        for (int i = 0; i < 12; i++) o[i] = 0.f;
        fence_f(o);
        if (__builtin_expect(unsafe, 0)) attn_safe(o, q, dK0, dK1, dV, bars, t);
        else if (tl == 0) attn_fast<true>(o, q, zz, dK0, dK1, dV, bars);
        else attn_fast<false>(o, q, zz, dK0, dK1, dV, bars);
        const float l0 = __shfl_sync(0xffffffff, o[8], (lane & ~3) | 2), l1 = __shfl_sync(0xffffffff, o[10], (lane & ~3) | 2);
        const float i0 = 1.f / l0, i1 = 1.f / l1;
        const int row0 = qq * 512 + (tl * 4 + wg) * 64 + wq * 16;
        bf16* op0 = g_O + (size_t)(row0 + g) * DM + head * 20 + 2 * t;
        bf16* op1 = op0 + 8 * DM;
        *(uint32_t*)(op0) = pack_bf16(o[0] * i0, o[1] * i0); *(uint32_t*)(op1) = pack_bf16(o[2] * i1, o[3] * i1);
        *(uint32_t*)(op0 + 8) = pack_bf16(o[4] * i0, o[5] * i0); *(uint32_t*)(op1 + 8) = pack_bf16(o[6] * i1, o[7] * i1);
        if (t < 2) { *(uint32_t*)(op0 + 16) = pack_bf16(o[8] * i0, o[9] * i0); *(uint32_t*)(op1 + 16) = pack_bf16(o[10] * i1, o[11] * i1); }
    }
}

constexpr int P3_NST = 6;
constexpr int P3_B = 102400;
constexpr int P3_A0 = P3_B;
constexpr int P3_MISC = P3_A0 + P3_NST * 16384;
constexpr int P3_SMEM = P3_MISC + 256 + 1024;
constexpr int P3_THREADS = 288;

__global__ void __launch_bounds__(P3_THREADS, 1)
p3_wo(const __grid_constant__ CUtensorMap tmO, const bf16* __restrict__ x, const bf16* __restrict__ wr) {
    extern __shared__ uint8_t smem_raw[];
    const uint32_t sb = (smem_u32(smem_raw) + 1023) & ~1023u;
    const int tid = threadIdx.x;
    const int warp = __shfl_sync(0xffffffff, tid >> 5, 0), lane = tid & 31;
    const int rank = blockIdx.x & 1, pr = blockIdx.x >> 1;
    const int j = 2 * (pr & 3) + rank, mt = pr >> 2;
    const uint32_t bar_full = sb + P3_MISC, bar_empty = bar_full + 64, bar_b = bar_full + 128;
    if (tid == 0) {
        for (int i = 0; i < P3_NST; i++) { mbar_init(bar_full + 8 * i, 1); mbar_init(bar_empty + 8 * i, 4); }
        mbar_init(bar_b, 1);
        fence_mbar_init();
        mbar_expect_tx(bar_b, P3_B);
        for (int c = 0; c < 10; c++) bulk_g2s(sb + c * 10240, g_wo + j * 102400 + c * 10240, 10240, bar_b);
    }
    __syncthreads();
    cluster_arrive(); cluster_wait();
    if (warp == 8) {
        if (lane == 0) {
            prefetch_tm(&tmO);
            pdl_wait();
            pdl_launch();
            #pragma unroll 1
            for (int it = 0; it < 10; it++) {
                const int s = it % P3_NST;
                if (it >= P3_NST) mbar_wait_cluster(bar_empty + 8 * s, 0);
                mbar_expect_tx(bar_full + 8 * s, 16384);
                tma2d_mc(sb + P3_A0 + s * 16384 + rank * 8192, &tmO, 64 * it, 128 * mt + 64 * rank, bar_full + 8 * s, 3);
            }
        }
        __syncwarp();
        cluster_arrive(); cluster_wait();
    } else {
        const int wg = warp >> 2, wq = warp & 3, g = lane >> 2, t = lane & 3;
        const int row = 128 * mt + 64 * wg + 16 * wq + g;
        const int col = 80 * j + 2 * t;
        uint32_t xr[20], wv[10];
        #pragma unroll
        for (int b = 0; b < 10; b++) {
            xr[2 * b] = __ldg((const uint32_t*)(x + (size_t)row * DM + col + 8 * b));
            xr[2 * b + 1] = __ldg((const uint32_t*)(x + (size_t)(row + 8) * DM + col + 8 * b));
            wv[b] = __ldg((const uint32_t*)(wr + col + 8 * b));
        }
        pdl_wait();
        float acc[40];
        mbar_wait(bar_b, 0);
        #pragma unroll 1
        for (int it = 0; it < 10; it++) {
            const int s = it % P3_NST;
            mbar_wait(bar_full + 8 * s, (it / P3_NST) & 1);
            const uint64_t da = mkdesc(sb + P3_A0 + s * 16384 + wg * 8192, 16, 1024, 1);
            const uint64_t db = mkdesc(sb + it * 10240, 1280, 128, 0);
            wg_fence();
            #pragma unroll
            for (int kk = 0; kk < 4; kk++) wg_ss80(acc, da + kk * 2, db + kk * 160, (it | kk) != 0);
            wg_commit();
            if (it >= 1) {
                wg_wait<1>();
                if (it <= 10 - P3_NST && (tid & 127) == 0) { const uint32_t e = bar_empty + 8 * ((it - 1) % P3_NST); mbar_arrive_cluster(e, 0); mbar_arrive_cluster(e, 1); }
            }
        }
        wg_wait<0>();
        fence_f(acc);
        float s0 = 0.f, q0 = 0.f, d0 = 0.f, s1 = 0.f, q1 = 0.f, d1 = 0.f;
        bf16* hp = g_h + (size_t)row * DM + col;
        #pragma unroll
        for (int b = 0; b < 10; b++) {
            const float h0 = bf_round(bf_lo(xr[2 * b]) + bf_round(acc[4 * b])), h1 = bf_round(bf_hi(xr[2 * b]) + bf_round(acc[4 * b + 1]));
            const float h2 = bf_round(bf_lo(xr[2 * b + 1]) + bf_round(acc[4 * b + 2])), h3 = bf_round(bf_hi(xr[2 * b + 1]) + bf_round(acc[4 * b + 3]));
            *(uint32_t*)(hp + 8 * b) = pack_bf16(h0, h1);
            *(uint32_t*)(hp + 8 * DM + 8 * b) = pack_bf16(h2, h3);
            const float w0 = bf_lo(wv[b]), w1 = bf_hi(wv[b]);
            s0 += h0 + h1; q0 = fmaf(h0, h0, fmaf(h1, h1, q0)); d0 = fmaf(h0, w0, fmaf(h1, w1, d0));
            s1 += h2 + h3; q1 = fmaf(h2, h2, fmaf(h3, h3, q1)); d1 = fmaf(h2, w0, fmaf(h3, w1, d1));
        }
        #pragma unroll
        for (int o = 1; o <= 2; o <<= 1) {
            s0 += __shfl_xor_sync(0xffffffff, s0, o); q0 += __shfl_xor_sync(0xffffffff, q0, o); d0 += __shfl_xor_sync(0xffffffff, d0, o);
            s1 += __shfl_xor_sync(0xffffffff, s1, o); q1 += __shfl_xor_sync(0xffffffff, q1, o); d1 += __shfl_xor_sync(0xffffffff, d1, o);
        }
        if (t < 3) {
            atomicAdd(&g_st[t * S_LEN + row], t == 0 ? s0 : (t == 1 ? q0 : d0));
            atomicAdd(&g_st[t * S_LEN + row + 8], t == 0 ? s1 : (t == 1 ? q1 : d1));
        }
        cluster_arrive(); cluster_wait();
    }
}

constexpr int P4_WG = 0;
constexpr int P4_WU = 20480;
constexpr int P4_WD = 40960;
constexpr int P4_XS = P4_WD + 16 * 1296;
constexpr int P4_RED = P4_XS + 2560;
constexpr int P4_ACT = P4_RED + 2048;
constexpr int P4_MISC = P4_ACT + 64;
constexpr int P4_SMEM = P4_MISC + 256;

__device__ __forceinline__ void cp_async16(uint32_t dst, const void* src) { asm volatile("cp.async.cg.shared.global [%0], [%1], 16;" :: "r"(dst), "l"(src) : "memory"); }
__device__ __forceinline__ void ldsm_x4_t(uint32_t& r0, uint32_t& r1, uint32_t& r2, uint32_t& r3, uint32_t a) {
    asm volatile("ldmatrix.sync.aligned.m8n8.x4.trans.shared.b16 {%0,%1,%2,%3}, [%4];" : "=r"(r0), "=r"(r1), "=r"(r2), "=r"(r3) : "r"(a) : "memory");
}
__device__ __forceinline__ void mma16816(float (&d)[4], uint32_t a0, uint32_t a2, uint32_t b0, uint32_t b1) {
    asm volatile("mma.sync.aligned.m16n8k16.row.col.f32.bf16.bf16.f32 {%0,%1,%2,%3}, {%4,%5,%6,%7}, {%8,%9}, {%0,%1,%2,%3};"
        : "+f"(d[0]), "+f"(d[1]), "+f"(d[2]), "+f"(d[3]) : "r"(a0), "r"(0u), "r"(a2), "r"(0u), "r"(b0), "r"(b1));
}
__device__ __forceinline__ void row_stats(int row, float sw, float& mu, float& rs, float& r) {
    const float sx = __ldcg(&g_st[row]), sq = __ldcg(&g_st[S_LEN + row]), dt = __ldcg(&g_st[2 * S_LEN + row]);
    mu = sx * (1.f / DM);
    const float var = fmaxf(sq * (1.f / DM) - mu * mu, 0.f);
    rs = 1.f / sqrtf(var + 1e-5f);
    r = rs * (dt - mu * sw);
}

__global__ void __launch_bounds__(256, 1)
p4_moe(const bf16* __restrict__ wr, const bf16* __restrict__ wgate, const bf16* __restrict__ wup, const bf16* __restrict__ wdown, bf16* __restrict__ out) {
    extern __shared__ __align__(128) uint8_t sm4[];
    const uint32_t sb = smem_u32(sm4);
    const int tid = threadIdx.x, warp = tid >> 5, lane = tid & 31;
    const int cta = blockIdx.x;
    const bool ffn = cta < 96;
    if (ffn) {
        const int f0 = 16 * cta;
        for (int i = tid; i < 1280; i += 256) {
            const int k = i >> 1, hf = i & 1;
            cp_async16(sb + P4_WG + k * 32 + hf * 16, wgate + (size_t)k * DFF + f0 + 8 * hf);
            cp_async16(sb + P4_WU + k * 32 + hf * 16, wup + (size_t)k * DFF + f0 + 8 * hf);
            const int kr = i / 80, c = i % 80;
            cp_async16(sb + P4_WD + kr * 1296 + c * 16, wdown + (size_t)(f0 + kr) * DM + c * 8);
        }
        asm volatile("cp.async.commit_group;" ::: "memory");
    }
    float sw = 0.f;
    for (int i = lane; i < DM / 2; i += 32) { const uint32_t u = __ldg((const uint32_t*)wr + i); sw += bf_lo(u) + bf_hi(u); }
    #pragma unroll
    for (int o = 16; o; o >>= 1) sw += __shfl_xor_sync(0xffffffff, sw, o);
    pdl_wait();
    uint4 hv[5];
    const int erow = 16 * cta + 2 * warp + (lane >> 4);
    #pragma unroll
    for (int i = 0; i < 5; i++) hv[i] = __ldcg((const uint4*)(g_h + (size_t)erow * DM) + (lane & 15) + 16 * i);
    uint32_t k1 = 0, k2 = 0;
    #pragma unroll
    for (int i = 0; i < 8; i++) {
        const int row = tid + 256 * i;
        float mu, rs, r; row_stats(row, sw, mu, rs, r);
        const uint32_t b = __bfloat16_as_ushort(__float2bfloat16_rn(r));
        const uint32_t ord = (b & 0x8000u) ? (~b & 0xFFFFu) : (b | 0x8000u);
        const uint32_t key = (ord << 16) | (uint32_t)(S_LEN - 1 - row);
        k2 = max(k2, min(k1, key)); k1 = max(k1, key);
    }
    {
        const uint32_t t1 = __reduce_max_sync(0xffffffff, k1);
        const uint32_t t2 = __reduce_max_sync(0xffffffff, k1 == t1 ? k2 : k1);
        uint32_t* sk = (uint32_t*)(sm4 + P4_MISC);
        if (lane == 0) { sk[2 * warp] = t1; sk[2 * warp + 1] = t2; }
    }
    {
        float mu, rs, r; row_stats(erow, sw, mu, rs, r);
        #pragma unroll
        for (int i = 0; i < 5; i++) {
            uint32_t u[4] = {hv[i].x, hv[i].y, hv[i].z, hv[i].w}, w[4];
            #pragma unroll
            for (int e = 0; e < 4; e++) {
                const float a = bf_lo(u[e]), b = bf_hi(u[e]);
                w[e] = pack_bf16(a + bf_round((a - mu) * rs), b + bf_round((b - mu) * rs));
            }
            *((uint4*)(out + (size_t)erow * DM) + (lane & 15) + 16 * i) = make_uint4(w[0], w[1], w[2], w[3]);
        }
    }
    __syncthreads();
    int idx0, idx1;
    {
        const uint32_t* sk = (const uint32_t*)(sm4 + P4_MISC);
        const uint32_t k = (lane < 16) ? sk[lane] : 0u;
        const uint32_t t1 = __reduce_max_sync(0xffffffff, k);
        const uint32_t t2 = __reduce_max_sync(0xffffffff, k == t1 ? 0u : k);
        idx0 = S_LEN - 1 - (int)(t1 & 0xFFFFu); idx1 = S_LEN - 1 - (int)(t2 & 0xFFFFu);
    }
    if (ffn) {
        if (tid < 160) {
            const int rsel = tid / 80, c = tid % 80, row = rsel ? idx1 : idx0;
            float mu, rs, r; row_stats(row, sw, mu, rs, r);
            const uint4 v = __ldcg((const uint4*)(g_h + (size_t)row * DM) + c);
            const uint32_t u[4] = {v.x, v.y, v.z, v.w}; uint32_t w[4];
            #pragma unroll
            for (int e = 0; e < 4; e++) w[e] = pack_bf16((bf_lo(u[e]) - mu) * rs, (bf_hi(u[e]) - mu) * rs);
            *(uint4*)(sm4 + P4_XS + rsel * 1280 + c * 16) = make_uint4(w[0], w[1], w[2], w[3]);
        }
        asm volatile("cp.async.wait_group 0;" ::: "memory");
        __syncthreads();
        const int g = lane >> 2, t = lane & 3;
        float ag[2][4] = {}, au[2][4] = {};
        #pragma unroll
        for (int ks = 0; ks < 5; ks++) {
            const int k0 = 16 * (5 * warp + ks);
            uint32_t a0 = 0, a2 = 0;
            if (g < 2) { a0 = *(const uint32_t*)(sm4 + P4_XS + g * 1280 + (k0 + 2 * t) * 2); a2 = *(const uint32_t*)(sm4 + P4_XS + g * 1280 + (k0 + 8 + 2 * t) * 2); }
            const uint32_t off = (k0 + (lane & 7) + ((lane >> 3) & 1) * 8) * 32 + (lane >> 4) * 16;
            uint32_t b0, b1, b2, b3;
            ldsm_x4_t(b0, b1, b2, b3, sb + P4_WG + off);
            mma16816(ag[0], a0, a2, b0, b1); mma16816(ag[1], a0, a2, b2, b3);
            ldsm_x4_t(b0, b1, b2, b3, sb + P4_WU + off);
            mma16816(au[0], a0, a2, b0, b1); mma16816(au[1], a0, a2, b2, b3);
        }
        float* red = (float*)(sm4 + P4_RED);
        if (g < 2) {
            float* p = red + warp * 64 + g * 32 + 2 * t;
            p[0] = ag[0][0]; p[1] = ag[0][1]; p[8] = ag[1][0]; p[9] = ag[1][1];
            p[16] = au[0][0]; p[17] = au[0][1]; p[24] = au[1][0]; p[25] = au[1][1];
        }
        __syncthreads();
        if (tid < 32) {
            const int rsel = tid >> 4, f = tid & 15;
            float gs = 0.f, us = 0.f;
            #pragma unroll
            for (int w = 0; w < 8; w++) { gs += red[w * 64 + rsel * 32 + f]; us += red[w * 64 + rsel * 32 + 16 + f]; }
            gs = bf_round(gs); us = bf_round(us);
            const float si = bf_round(gs / (1.f + __expf(-gs)));
            ((bf16*)(sm4 + P4_ACT))[rsel * 16 + f] = __float2bfloat16_rn(si * us);
        }
        __syncthreads();
        uint32_t a0 = 0, a2 = 0;
        if (g < 2) { a0 = *(const uint32_t*)(sm4 + P4_ACT + g * 32 + 4 * t); a2 = *(const uint32_t*)(sm4 + P4_ACT + g * 32 + 16 + 4 * t); }
        #pragma unroll
        for (int i = 0; i < 5; i++) {
            const int n0 = 80 * warp + 16 * i;
            const uint32_t ad = sb + P4_WD + ((lane & 7) + ((lane >> 3) & 1) * 8) * 1296 + (n0 + (lane >> 4) * 8) * 2;
            uint32_t b0, b1, b2, b3;
            ldsm_x4_t(b0, b1, b2, b3, ad);
            float y0[4] = {}, y1[4] = {};
            mma16816(y0, a0, a2, b0, b1); mma16816(y1, a0, a2, b2, b3);
            if (g < 2) {
                float* yp = g_y + g * DM + n0 + 2 * t;
                atomicAdd(yp, y0[0]); atomicAdd(yp + 1, y0[1]); atomicAdd(yp + 8, y1[0]); atomicAdd(yp + 9, y1[1]);
            }
        }
    }
    __shared__ unsigned s_last;
    __threadfence();
    __syncthreads();
    if (tid == 0) s_last = (atomicAdd(&g_cnt4, 1) == gridDim.x - 1);
    __syncthreads();
    if (s_last) {
        __threadfence();
        for (int i = tid; i < 2 * DM / 2; i += 256) {
            const int rsel = i / (DM / 2), c = 2 * (i % (DM / 2)), row = rsel ? idx1 : idx0;
            float mu, rs, r; row_stats(row, sw, mu, rs, r);
            const float sg = bf_round(1.f / (1.f + __expf(-bf_round(r))));
            const uint32_t u = __ldcg((const uint32_t*)(g_h + (size_t)row * DM + c));
            const float h0 = bf_lo(u), h1 = bf_hi(u);
            const float y0 = bf_round(bf_round(__ldcg(&g_y[rsel * DM + c])) * sg), y1 = bf_round(bf_round(__ldcg(&g_y[rsel * DM + c + 1])) * sg);
            const float z0 = bf_round(bf_round((h0 - mu) * rs) + y0), z1 = bf_round(bf_round((h1 - mu) * rs) + y1);
            *(uint32_t*)(out + (size_t)row * DM + c) = pack_bf16(h0 + z0, h1 + z1);
        }
    }
}

typedef CUresult (*EncodeFn)(CUtensorMap*, CUtensorMapDataType, cuuint32_t, void*, const cuuint64_t*, const cuuint64_t*, const cuuint32_t*, const cuuint32_t*,
                             CUtensorMapInterleave, CUtensorMapSwizzle, CUtensorMapL2promotion, CUtensorMapFloatOOBfill);

static void make_map(EncodeFn enc, CUtensorMap* tm, const void* ptr, uint64_t inner, uint64_t outer, uint32_t box_in, uint32_t box_out) {
    cuuint64_t dims[2] = {inner, outer};
    cuuint64_t strides[1] = {inner * 2};
    cuuint32_t box[2] = {box_in, box_out};
    cuuint32_t es[2] = {1, 1};
    enc(tm, CU_TENSOR_MAP_DATA_TYPE_BFLOAT16, 2, const_cast<void*>(ptr), dims, strides, box, es, CU_TENSOR_MAP_INTERLEAVE_NONE,
        CU_TENSOR_MAP_SWIZZLE_128B, CU_TENSOR_MAP_L2_PROMOTION_L2_256B, CU_TENSOR_MAP_FLOAT_OOB_FILL_NONE);
}

template<typename... KArgs, typename... Args>
static void launch(void (*kern)(KArgs...), int grid, int block, int smem, int cluster, bool pdl, Args... args) {
    cudaLaunchConfig_t cfg = {};
    cfg.gridDim = dim3(grid); cfg.blockDim = dim3(block); cfg.dynamicSmemBytes = smem; cfg.stream = cudaStreamPerThread;
    cudaLaunchAttribute at[2]; int na = 0;
    if (cluster > 1) { at[na].id = cudaLaunchAttributeClusterDimension; at[na].val.clusterDim.x = cluster; at[na].val.clusterDim.y = 1; at[na].val.clusterDim.z = 1; na++; }
    if (pdl) { at[na].id = cudaLaunchAttributeProgrammaticStreamSerialization; at[na].val.programmaticStreamSerializationAllowed = 1; na++; }
    cfg.attrs = at; cfg.numAttrs = na;
    cudaLaunchKernelEx(&cfg, kern, KArgs(args)...);
}

#define KMASK 15

extern "C" void kernel_launch(void* const* d_in, const int* in_sizes, int n_in, void* d_out, int out_size) {
    const bf16* x = (const bf16*)d_in[0];
    const bf16* wqkv = (const bf16*)d_in[1];
    const bf16* wo = (const bf16*)d_in[2];
    const bf16* wr = (const bf16*)d_in[4];
    const bf16* wgate = (const bf16*)d_in[5];
    const bf16* wup = (const bf16*)d_in[6];
    const bf16* wdown = (const bf16*)d_in[7];
    static bool init = false;
    static EncodeFn enc = nullptr;
    static void* pO = nullptr;
    if (!init) {
        void* fn = nullptr; cudaDriverEntryPointQueryResult qr;
        cudaGetDriverEntryPoint("cuTensorMapEncodeTiled", &fn, cudaEnableDefault, &qr);
        enc = (EncodeFn)fn;
        cudaGetSymbolAddress(&pO, g_O);
        cudaFuncSetAttribute(p1_qkv, cudaFuncAttributeMaxDynamicSharedMemorySize, P1_SMEM);
        cudaFuncSetAttribute(p2_attn, cudaFuncAttributeMaxDynamicSharedMemorySize, P2_SMEM);
        cudaFuncSetAttribute(p3_wo, cudaFuncAttributeMaxDynamicSharedMemorySize, P3_SMEM);
        cudaFuncSetAttribute(p4_moe, cudaFuncAttributeMaxDynamicSharedMemorySize, P4_SMEM);
        init = true;
    }
    CUtensorMap tmX, tmW, tmO;
    make_map(enc, &tmX, x, DM, S_LEN, 64, 128);
    make_map(enc, &tmW, wqkv, 3 * DM, DM, 64, 64);
    make_map(enc, &tmO, pO, DM, S_LEN, 64, 64);
    if (KMASK & 1) launch(p1_qkv, 132, P1_THREADS, P1_SMEM, 2, false, tmX, tmW, wo);
    if (KMASK & 2) launch(p2_attn, 132, 512, P2_SMEM, 1, true, wgate, wup, wdown);
    if (KMASK & 4) launch(p3_wo, 128, P3_THREADS, P3_SMEM, 2, true, tmO, x, wr);
    if (KMASK & 8) launch(p4_moe, 128, 256, P4_SMEM, 1, true, wr, wgate, wup, wdown, (bf16*)d_out);
}
```

```cpp
#include <cuda_runtime.h>
#include <cuda_bf16.h>
#include <cuda.h>
#include <stdint.h>

typedef __nv_bfloat16 bf16;

constexpr int S_LEN = 2048, DM = 640, NHEAD = 32, DFF = 1536;
constexpr int UNIT_BYTES = 98304;
#define PMASK 0xDADA
constexpr uint32_t POLY_MASK = PMASK;
constexpr float QSCALE = 0.22360679774997896f * 1.4426950408889634f;

#define KG1 1
#define KG2 3
#define KG3 8
__device__ __align__(1024) uint8_t g_img[96 * UNIT_BYTES];
__device__ __align__(1024) uint64_t g_p1_col[4 * 3 * DM];
__device__ __align__(256) float g_kmax[NHEAD * 64];
__device__ __align__(1024) uint8_t g_O[S_LEN * DM * 2];
__device__ __align__(1024) uint8_t g_wo[8 * 102400];
__device__ unsigned g_epoch;
__device__ __align__(1024) uint4 g_ll[65536];
#define g_ll_st (g_ll)
#define g_ll_y (g_ll + 16384)
#define g_ll_row ((uint64_t*)(g_ll + 59392))
#define g_ll_key ((uint64_t*)(g_ll + 64512))
#define g_ll_sc (g_ll + 65024)
__device__ __align__(1024) unsigned g_cnt[272 * 32];
__device__ __align__(1024) uint8_t g_wgu[96 * 40960];

#define SPIN_LIM (1u << 20)
#define EXP_ORDER 0
__device__ __forceinline__ uint32_t smem_u32(const void* p) { return (uint32_t)__cvta_generic_to_shared(p); }
__device__ __forceinline__ uint64_t mkdesc(uint32_t addr, uint32_t lbo, uint32_t sbo, uint32_t swz) {
    return (uint64_t)((addr & 0x3FFFF) >> 4) | ((uint64_t)(lbo >> 4) << 16) | ((uint64_t)(sbo >> 4) << 32) | ((uint64_t)swz << 62);
}
__device__ __forceinline__ void wg_fence() { asm volatile("wgmma.fence.sync.aligned;" ::: "memory"); }
__device__ __forceinline__ void wg_commit() { asm volatile("wgmma.commit_group.sync.aligned;" ::: "memory"); }
template<int N> __device__ __forceinline__ void wg_wait() { asm volatile("wgmma.wait_group.sync.aligned %0;" :: "n"(N) : "memory"); }
__device__ __forceinline__ void mbar_init(uint32_t bar, uint32_t cnt) { asm volatile("mbarrier.init.shared::cta.b64 [%0], %1;" :: "r"(bar), "r"(cnt) : "memory"); }
__device__ __forceinline__ void mbar_expect_tx(uint32_t bar, uint32_t bytes) { asm volatile("mbarrier.arrive.expect_tx.shared::cta.b64 _, [%0], %1;" :: "r"(bar), "r"(bytes) : "memory"); }
__device__ __forceinline__ void mbar_arrive(uint32_t bar) { asm volatile("mbarrier.arrive.shared::cta.b64 _, [%0];" :: "r"(bar) : "memory"); }
__device__ __forceinline__ void mbar_arrive_cluster(uint32_t bar, uint32_t cta) {
    asm volatile("{.reg .b32 ra; mapa.shared::cluster.u32 ra, %0, %1; mbarrier.arrive.release.cluster.shared::cluster.b64 _, [ra];}" :: "r"(bar), "r"(cta) : "memory");
}
__device__ __forceinline__ bool mbar_try(uint32_t bar, uint32_t parity) {
    uint32_t ok;
    asm volatile("{.reg .pred p; mbarrier.try_wait.parity.shared::cta.b64 p, [%1], %2; selp.u32 %0, 1, 0, p;}" : "=r"(ok) : "r"(bar), "r"(parity) : "memory");
    return ok;
}
__device__ __forceinline__ bool mbar_try_cluster(uint32_t bar, uint32_t parity) {
    uint32_t ok;
    asm volatile("{.reg .pred p; mbarrier.try_wait.parity.acquire.cluster.shared::cta.b64 p, [%1], %2; selp.u32 %0, 1, 0, p;}" : "=r"(ok) : "r"(bar), "r"(parity) : "memory");
    return ok;
}
__device__ __forceinline__ void mbar_wait(uint32_t bar, uint32_t parity) {
    if (mbar_try(bar, parity)) return;
    uint32_t n = 0;
    while (!mbar_try(bar, parity)) { if (++n > SPIN_LIM) break; }
}
__device__ __forceinline__ void mbar_wait_cluster(uint32_t bar, uint32_t parity) {
    uint32_t n = 0;
    while (!mbar_try_cluster(bar, parity)) { if (++n > SPIN_LIM) break; }
}
__device__ __forceinline__ void fence_mbar_init() { asm volatile("fence.mbarrier_init.release.cluster;" ::: "memory"); }
__device__ __forceinline__ void fence_proxy_async_global() { asm volatile("fence.proxy.async.global;" ::: "memory"); }
__device__ __forceinline__ void st_release(unsigned* p, unsigned v) { asm volatile("st.release.gpu.global.u32 [%0], %1;" :: "l"(p), "r"(v) : "memory"); }
__device__ __forceinline__ void fence_proxy_async() { asm volatile("fence.proxy.async.shared::cta;" ::: "memory"); }
__device__ __forceinline__ void cluster_arrive() { asm volatile("barrier.cluster.arrive.release.aligned;" ::: "memory"); }
__device__ __forceinline__ void cluster_wait() { asm volatile("barrier.cluster.wait.acquire.aligned;" ::: "memory"); }
__device__ __forceinline__ void bar_sync(int id, int n) { asm volatile("bar.sync %0, %1;" :: "r"(id), "r"(n) : "memory"); }
__device__ __forceinline__ void pdl_wait() { asm volatile("griddepcontrol.wait;" ::: "memory"); }
__device__ __forceinline__ void pdl_launch() { asm volatile("griddepcontrol.launch_dependents;" ::: "memory"); }
__device__ __forceinline__ void bulk_g2s(uint32_t dst, const void* src, uint32_t bytes, uint32_t bar) {
    asm volatile("cp.async.bulk.shared::cluster.global.mbarrier::complete_tx::bytes [%0], [%1], %2, [%3];" :: "r"(dst), "l"(src), "r"(bytes), "r"(bar) : "memory");
}
__device__ __forceinline__ void bulk_s2g(void* dst, uint32_t src, uint32_t bytes) {
    asm volatile("cp.async.bulk.global.shared::cta.bulk_group [%0], [%1], %2;" :: "l"(dst), "r"(src), "r"(bytes) : "memory");
}
__device__ __forceinline__ void tma2d(uint32_t dst, const CUtensorMap* tm, int x, int y, uint32_t bar) {
    asm volatile("cp.async.bulk.tensor.2d.shared::cluster.global.mbarrier::complete_tx::bytes [%0], [%1, {%2, %3}], [%4];"
        :: "r"(dst), "l"(tm), "r"(x), "r"(y), "r"(bar) : "memory");
}
__device__ __forceinline__ void tma2d_mc(uint32_t dst, const CUtensorMap* tm, int x, int y, uint32_t bar, uint16_t mask) {
    asm volatile("cp.async.bulk.tensor.2d.shared::cluster.global.mbarrier::complete_tx::bytes.multicast::cluster [%0], [%1, {%2, %3}], [%4], %5;"
        :: "r"(dst), "l"(tm), "r"(x), "r"(y), "r"(bar), "h"(mask) : "memory");
}
__device__ __forceinline__ void tma2d_e(uint32_t dst, const CUtensorMap* tm, int x, int y, uint32_t bar) {
    asm volatile("{.reg .pred p; elect.sync _|p, 0xffffffff;\n"
        "@p cp.async.bulk.tensor.2d.shared::cluster.global.mbarrier::complete_tx::bytes [%0], [%1, {%2, %3}], [%4];}"
        :: "r"(dst), "l"(tm), "r"(x), "r"(y), "r"(bar) : "memory");
}
__device__ __forceinline__ void mbar_expect_tx_e(uint32_t bar, uint32_t bytes) {
    asm volatile("{.reg .pred p; elect.sync _|p, 0xffffffff; @p mbarrier.arrive.expect_tx.shared::cta.b64 _, [%0], %1;}" :: "r"(bar), "r"(bytes) : "memory");
}
__device__ __forceinline__ void bulk_g2s_e(uint32_t dst, const void* src, uint32_t bytes, uint32_t bar) {
    asm volatile("{.reg .pred p; elect.sync _|p, 0xffffffff;\n"
        "@p cp.async.bulk.shared::cluster.global.mbarrier::complete_tx::bytes [%0], [%1], %2, [%3];}" :: "r"(dst), "l"(src), "r"(bytes), "r"(bar) : "memory");
}
__device__ __forceinline__ void bulk_s2g_e(void* dst, uint32_t src, uint32_t bytes) {
    asm volatile("{.reg .pred p; elect.sync _|p, 0xffffffff; @p cp.async.bulk.global.shared::cta.bulk_group [%0], [%1], %2;}" :: "l"(dst), "r"(src), "r"(bytes) : "memory");
}
__device__ __forceinline__ void prefetch_tm(const CUtensorMap* tm) { asm volatile("prefetch.tensormap [%0];" :: "l"(tm) : "memory"); }
template<int N> __device__ __forceinline__ void fence_f(float (&d)[N]) {
    #pragma unroll
    for (int i = 0; i < N; i++) asm volatile("" : "+f"(d[i]) :: "memory");
}
template<int N> __device__ __forceinline__ void fence_u(uint32_t (&d)[N]) {
    #pragma unroll
    for (int i = 0; i < N; i++) asm volatile("" : "+r"(d[i]) :: "memory");
}
__device__ __forceinline__ float ex2f(float x) { float y; asm("ex2.approx.ftz.f32 %0, %1;" : "=f"(y) : "f"(x)); return y; }
__device__ __forceinline__ uint32_t pack_bf16(float lo, float hi) { uint32_t r; asm("cvt.rn.bf16x2.f32 %0, %1, %2;" : "=r"(r) : "f"(hi), "f"(lo)); return r; }
__device__ __forceinline__ float bf_lo(uint32_t u) { return __uint_as_float(u << 16); }
__device__ __forceinline__ float bf_hi(uint32_t u) { return __uint_as_float(u & 0xffff0000u); }
__device__ __forceinline__ float bf_round(float x) { return __bfloat162float(__float2bfloat16_rn(x)); }
__device__ __forceinline__ unsigned ld_acquire(const unsigned* p) { unsigned v; asm volatile("ld.acquire.gpu.global.u32 %0, [%1];" : "=r"(v) : "l"(p) : "memory"); return v; }
__device__ __forceinline__ void red_release(unsigned* p, unsigned v) { asm volatile("red.release.gpu.global.add.u32 [%0], %1;" :: "l"(p), "r"(v) : "memory"); }
__device__ __forceinline__ void spin_until(const unsigned* p, unsigned target) {
    uint32_t n = 0;
    while (ld_acquire(p) < target) { if (++n > SPIN_LIM) break; }
}
__device__ __forceinline__ void red_relaxed(unsigned* p, unsigned v) { asm volatile("red.relaxed.gpu.global.add.u32 [%0], %1;" :: "l"(p), "r"(v) : "memory"); }
__device__ __forceinline__ void fence_gpu() { asm volatile("fence.acq_rel.gpu;" ::: "memory"); }
__device__ __forceinline__ void spin_cnt(const unsigned* p, unsigned target) {
    uint32_t n = 0;
    while ((int)(ld_acquire(p) - target) < 0) { if (++n > SPIN_LIM) break; }
}
__device__ __forceinline__ void st_ll(uint64_t* p, uint32_t v, uint32_t tag) { asm volatile("st.relaxed.gpu.global.b64 [%0], %1;" :: "l"(p), "l"(((uint64_t)tag << 32) | v) : "memory"); }
__device__ __forceinline__ uint64_t ld_ll1(const uint64_t* p) { uint64_t v; asm volatile("ld.relaxed.gpu.global.b64 %0, [%1];" : "=l"(v) : "l"(p) : "memory"); return v; }
__device__ __forceinline__ void ld_ll2(uint64_t& a, uint64_t& b, const uint64_t* p) { asm volatile("ld.relaxed.gpu.global.v2.b64 {%0, %1}, [%2];" : "=l"(a), "=l"(b) : "l"(p) : "memory"); }
__device__ __forceinline__ void st_ll4(uint4* p, uint32_t a, uint32_t b, uint32_t c, uint32_t tag) {
    asm volatile("{.reg .b128 v; mov.b128 v, {%1, %2}; st.relaxed.gpu.global.b128 [%0], v;}" :: "l"(p), "l"(((uint64_t)b << 32) | a), "l"(((uint64_t)tag << 32) | c) : "memory");
}
__device__ __forceinline__ uint4 ld_ll4(const uint4* p) {
    uint64_t a, b;
    asm volatile("{.reg .b128 v; ld.relaxed.gpu.global.b128 v, [%2]; mov.b128 {%0, %1}, v;}" : "=l"(a), "=l"(b) : "l"(p) : "memory");
    return make_uint4((uint32_t)a, (uint32_t)(a >> 32), (uint32_t)b, (uint32_t)(b >> 32));
}
__device__ __forceinline__ uint32_t add_bf16x2(uint32_t a, uint32_t b) { uint32_t r; asm("add.rn.bf16x2 %0, %1, %2;" : "=r"(r) : "r"(a), "r"(b)); return r; }
__device__ __forceinline__ uint4 lds128(uint32_t a) { uint4 v; asm volatile("ld.shared.v4.u32 {%0,%1,%2,%3}, [%4];" : "=r"(v.x), "=r"(v.y), "=r"(v.z), "=r"(v.w) : "r"(a)); return v; }
__device__ __forceinline__ uint32_t lds32(uint32_t a) { uint32_t v; asm volatile("ld.shared.u32 %0, [%1];" : "=r"(v) : "r"(a) : "memory"); return v; }
__device__ __forceinline__ void sts32(uint32_t a, uint32_t v) { asm volatile("st.shared.u32 [%0], %1;" :: "r"(a), "r"(v) : "memory"); }
__device__ __forceinline__ void sts64(uint32_t a, uint32_t v0, uint32_t v1) { asm volatile("st.shared.v2.u32 [%0], {%1,%2};" :: "r"(a), "r"(v0), "r"(v1) : "memory"); }

template<int N> __device__ __forceinline__ void reg_inc() { asm volatile("setmaxnreg.inc.sync.aligned.u32 %0;" :: "n"(N)); }
template<int N> __device__ __forceinline__ void reg_dec() { asm volatile("setmaxnreg.dec.sync.aligned.u32 %0;" :: "n"(N)); }
__device__ __forceinline__ void ldsm4(uint32_t* r, uint32_t a) {
    asm volatile("ldmatrix.sync.aligned.m8n8.x4.shared.b16 {%0,%1,%2,%3}, [%4];" : "=r"(r[0]), "=r"(r[1]), "=r"(r[2]), "=r"(r[3]) : "r"(a) : "memory");
}

constexpr int SM_MISC = 225280;
constexpr int SM_Q = 196608;
constexpr int B1_FULL = SM_MISC, B1_EMPTY = SM_MISC + 32, B1_GO = SM_MISC + 64, B1_READY = SM_MISC + 72, B1_FREE = SM_MISC + 80, B1_STAGED = SM_MISC + 88, B1_END = SM_MISC + 112;
constexpr int B2_KV = SM_MISC + 128;
constexpr int B2_CONST = SM_MISC + 272, B2_HI = SM_MISC + 288, B2_DONE = SM_MISC + 352, B2_T0 = SM_MISC + 368;
constexpr int B2_MID = SM_MISC + 376, B2_FIRST = SM_MISC + 380, B2_GRP = SM_MISC + 384;
constexpr int B3_FULL = SM_MISC + 400, B3_EMPTY = SM_MISC + 528, B3_B = SM_MISC + 592, B3_W1 = SM_MISC + 600, B3_W2 = SM_MISC + 608;
constexpr int B2_KM = SM_MISC + 616, B2_Q = SM_MISC + 624;
constexpr int SM_KEYS = SM_MISC + 640;
constexpr int SM_BUF = SM_MISC + 768;
constexpr int SM_KM = SM_BUF + 2560;
constexpr int SM_TOTAL = SM_BUF + 2560 + 2048 + 64 + 1024;
constexpr int NTHREADS = 512;

#define DBG_R(v) do {} while (0)
#define DBG_W(k, i, v) do {} while (0)
#define DBG_T(k, i) do {} while (0)
template<int SC> __device__ __forceinline__ void wg_rs128t(float (&d)[64], uint32_t a0, uint32_t a1, uint32_t a2, uint32_t a3, uint64_t db) {
    asm volatile("wgmma.mma_async.sync.aligned.m64n128k16.f32.bf16.bf16 {%0,%1,%2,%3,%4,%5,%6,%7,%8,%9,%10,%11,%12,%13,%14,%15,%16,%17,%18,%19,%20,%21,%22,%23,%24,%25,%26,%27,%28,%29,%30,%31,%32,%33,%34,%35,%36,%37,%38,%39,%40,%41,%42,%43,%44,%45,%46,%47,%48,%49,%50,%51,%52,%53,%54,%55,%56,%57,%58,%59,%60,%61,%62,%63}, {%64,%65,%66,%67}, %68, %69, 1, 1, 1;"
        : "+f"(d[0]),"+f"(d[1]),"+f"(d[2]),"+f"(d[3]),"+f"(d[4]),"+f"(d[5]),"+f"(d[6]),"+f"(d[7]),"+f"(d[8]),"+f"(d[9]),"+f"(d[10]),"+f"(d[11]),"+f"(d[12]),"+f"(d[13]),"+f"(d[14]),"+f"(d[15]),"+f"(d[16]),"+f"(d[17]),"+f"(d[18]),"+f"(d[19]),"+f"(d[20]),"+f"(d[21]),"+f"(d[22]),"+f"(d[23]),"+f"(d[24]),"+f"(d[25]),"+f"(d[26]),"+f"(d[27]),"+f"(d[28]),"+f"(d[29]),"+f"(d[30]),"+f"(d[31]),"+f"(d[32]),"+f"(d[33]),"+f"(d[34]),"+f"(d[35]),"+f"(d[36]),"+f"(d[37]),"+f"(d[38]),"+f"(d[39]),"+f"(d[40]),"+f"(d[41]),"+f"(d[42]),"+f"(d[43]),"+f"(d[44]),"+f"(d[45]),"+f"(d[46]),"+f"(d[47]),"+f"(d[48]),"+f"(d[49]),"+f"(d[50]),"+f"(d[51]),"+f"(d[52]),"+f"(d[53]),"+f"(d[54]),"+f"(d[55]),"+f"(d[56]),"+f"(d[57]),"+f"(d[58]),"+f"(d[59]),"+f"(d[60]),"+f"(d[61]),"+f"(d[62]),"+f"(d[63])
        : "r"(a0), "r"(a1), "r"(a2), "r"(a3), "l"(db), "n"(SC));
}
template<int SC> __device__ __forceinline__ void wg_rs112t(float (&d)[56], uint32_t a0, uint32_t a1, uint32_t a2, uint32_t a3, uint64_t db) {
    asm volatile("wgmma.mma_async.sync.aligned.m64n112k16.f32.bf16.bf16 {%0,%1,%2,%3,%4,%5,%6,%7,%8,%9,%10,%11,%12,%13,%14,%15,%16,%17,%18,%19,%20,%21,%22,%23,%24,%25,%26,%27,%28,%29,%30,%31,%32,%33,%34,%35,%36,%37,%38,%39,%40,%41,%42,%43,%44,%45,%46,%47,%48,%49,%50,%51,%52,%53,%54,%55}, {%56,%57,%58,%59}, %60, %61, 1, 1, 1;"
        : "+f"(d[0]),"+f"(d[1]),"+f"(d[2]),"+f"(d[3]),"+f"(d[4]),"+f"(d[5]),"+f"(d[6]),"+f"(d[7]),"+f"(d[8]),"+f"(d[9]),"+f"(d[10]),"+f"(d[11]),"+f"(d[12]),"+f"(d[13]),"+f"(d[14]),"+f"(d[15]),"+f"(d[16]),"+f"(d[17]),"+f"(d[18]),"+f"(d[19]),"+f"(d[20]),"+f"(d[21]),"+f"(d[22]),"+f"(d[23]),"+f"(d[24]),"+f"(d[25]),"+f"(d[26]),"+f"(d[27]),"+f"(d[28]),"+f"(d[29]),"+f"(d[30]),"+f"(d[31]),"+f"(d[32]),"+f"(d[33]),"+f"(d[34]),"+f"(d[35]),"+f"(d[36]),"+f"(d[37]),"+f"(d[38]),"+f"(d[39]),"+f"(d[40]),"+f"(d[41]),"+f"(d[42]),"+f"(d[43]),"+f"(d[44]),"+f"(d[45]),"+f"(d[46]),"+f"(d[47]),"+f"(d[48]),"+f"(d[49]),"+f"(d[50]),"+f"(d[51]),"+f"(d[52]),"+f"(d[53]),"+f"(d[54]),"+f"(d[55])
        : "r"(a0), "r"(a1), "r"(a2), "r"(a3), "l"(db), "n"(SC));
}
template<int SC> __device__ __forceinline__ void wg_rs80t(float (&d)[40], uint32_t a0, uint32_t a1, uint32_t a2, uint32_t a3, uint64_t db) {
    asm volatile("wgmma.mma_async.sync.aligned.m64n80k16.f32.bf16.bf16 {%0,%1,%2,%3,%4,%5,%6,%7,%8,%9,%10,%11,%12,%13,%14,%15,%16,%17,%18,%19,%20,%21,%22,%23,%24,%25,%26,%27,%28,%29,%30,%31,%32,%33,%34,%35,%36,%37,%38,%39}, {%40,%41,%42,%43}, %44, %45, 1, 1, 1;"
        : "+f"(d[0]),"+f"(d[1]),"+f"(d[2]),"+f"(d[3]),"+f"(d[4]),"+f"(d[5]),"+f"(d[6]),"+f"(d[7]),"+f"(d[8]),"+f"(d[9]),"+f"(d[10]),"+f"(d[11]),"+f"(d[12]),"+f"(d[13]),"+f"(d[14]),"+f"(d[15]),"+f"(d[16]),"+f"(d[17]),"+f"(d[18]),"+f"(d[19]),"+f"(d[20]),"+f"(d[21]),"+f"(d[22]),"+f"(d[23]),"+f"(d[24]),"+f"(d[25]),"+f"(d[26]),"+f"(d[27]),"+f"(d[28]),"+f"(d[29]),"+f"(d[30]),"+f"(d[31]),"+f"(d[32]),"+f"(d[33]),"+f"(d[34]),"+f"(d[35]),"+f"(d[36]),"+f"(d[37]),"+f"(d[38]),"+f"(d[39])
        : "r"(a0), "r"(a1), "r"(a2), "r"(a3), "l"(db), "n"(SC));
}
template<int SC> __device__ __forceinline__ void wg_rs64(float (&d)[32], uint32_t a0, uint32_t a1, uint32_t a2, uint32_t a3, uint64_t db) {
    asm volatile("wgmma.mma_async.sync.aligned.m64n64k16.f32.bf16.bf16 {%0,%1,%2,%3,%4,%5,%6,%7,%8,%9,%10,%11,%12,%13,%14,%15,%16,%17,%18,%19,%20,%21,%22,%23,%24,%25,%26,%27,%28,%29,%30,%31}, {%32,%33,%34,%35}, %36, %37, 1, 1, 0;"
        : "+f"(d[0]),"+f"(d[1]),"+f"(d[2]),"+f"(d[3]),"+f"(d[4]),"+f"(d[5]),"+f"(d[6]),"+f"(d[7]),"+f"(d[8]),"+f"(d[9]),"+f"(d[10]),"+f"(d[11]),"+f"(d[12]),"+f"(d[13]),"+f"(d[14]),"+f"(d[15]),"+f"(d[16]),"+f"(d[17]),"+f"(d[18]),"+f"(d[19]),"+f"(d[20]),"+f"(d[21]),"+f"(d[22]),"+f"(d[23]),"+f"(d[24]),"+f"(d[25]),"+f"(d[26]),"+f"(d[27]),"+f"(d[28]),"+f"(d[29]),"+f"(d[30]),"+f"(d[31])
        : "r"(a0), "r"(a1), "r"(a2), "r"(a3), "l"(db), "n"(SC));
}
template<int SC> __device__ __forceinline__ void wg_pv24(float (&d)[12], uint32_t a0, uint32_t a1, uint32_t a2, uint32_t a3, uint64_t db) {
    asm volatile("wgmma.mma_async.sync.aligned.m64n24k16.f32.bf16.bf16 {%0,%1,%2,%3,%4,%5,%6,%7,%8,%9,%10,%11}, {%12,%13,%14,%15}, %16, %17, 1, 1, 1;"
        : "+f"(d[0]),"+f"(d[1]),"+f"(d[2]),"+f"(d[3]),"+f"(d[4]),"+f"(d[5]),"+f"(d[6]),"+f"(d[7]),"+f"(d[8]),"+f"(d[9]),"+f"(d[10]),"+f"(d[11])
        : "r"(a0), "r"(a1), "r"(a2), "r"(a3), "l"(db), "n"(SC));
}

#define P1_PRE 2
#define P1_STAG 0
#define HELP_WAIT 1
#define EPI_B 5
constexpr int P1_STAGE = 49152;
constexpr int P1_STG = 2 * P1_STAGE;

__device__ __forceinline__ void p1_issue(uint32_t sb, const CUtensorMap* tmX, const CUtensorMap* tmW, int mt, int j, int it) {
    const int s = it & 3;
    const uint32_t st = sb + s * P1_STAGE, fb = sb + B1_FULL + 8 * s;
    mbar_expect_tx_e(fb, P1_STAGE);
    tma2d_e(st, tmX, 64 * it, 128 * mt, fb);
    #pragma unroll
    for (int q = 0; q < 4; q++) tma2d_e(st + 16384 + q * 8192, tmW, 240 * j + 64 * q, 64 * it, fb);
}

__device__ __forceinline__ void kv_issue_rest(const uint32_t sb, const int head, const int qq) {
    const uint8_t* gk = g_img + (size_t)(32 + head) * UNIT_BYTES;
    mbar_wait(sb + B2_KV, 0);
    #pragma unroll
    for (int gI = 1; gI < 4; gI++) {
        const int c0 = gI == 1 ? KG1 : gI == 2 ? KG2 : KG3, nc = (gI == 1 ? KG2 : gI == 2 ? KG3 : 16) - c0;
        if (nc > 0) {
            mbar_expect_tx_e(sb + B2_KV + 8 * c0, nc * 12288);
            bulk_g2s_e(sb + c0 * 6144, gk + c0 * 6144, nc * 6144, sb + B2_KV + 8 * c0);
            bulk_g2s_e(sb + 98304 + c0 * 6144, gk + (size_t)32 * UNIT_BYTES + c0 * 6144, nc * 6144, sb + B2_KV + 8 * c0);
        }
    }
    mbar_expect_tx_e(sb + B2_Q + 8, 12288);
    bulk_g2s_e(sb + SM_Q + 12288, g_img + (size_t)head * UNIT_BYTES + qq * 24576 + 12288, 12288, sb + B2_Q + 8);
}

__device__ __forceinline__ void p1_phase(const uint32_t sb, const int tid, const int warp, const int lane, const int wgi, const int b, const int mt, const int j, const uint32_t tag,
                                         const CUtensorMap* tmX, const CUtensorMap* tmW, const bf16* __restrict__ wqkv) {
    const uint32_t bar_full = sb + B1_FULL, bar_empty = sb + B1_EMPTY, bar_go = sb + B1_GO, bar_ready = sb + B1_READY, bar_free = sb + B1_FREE, bar_staged = sb + B1_STAGED;
    const uint32_t s_cs = sb + SM_BUF, s_red = s_cs + 1024;
    unsigned* cnt = g_cnt + 32 * j;
    if (wgi == 0) {
        reg_dec<56>();
        if (warp == 0) {
            if (P1_PRE < 4) {
                #pragma unroll
                for (int it = P1_PRE; it < 4; it++) {
                    if (it == P1_PRE || P1_STAG) mbar_wait(bar_full + 8 * (it - P1_PRE), 0);
                    p1_issue(sb, tmX, tmW, mt, j, it);
                }
            }
            #pragma unroll 1
            for (int it = 4; it < 10; it++) {
                mbar_wait(bar_empty + 8 * (it & 3), ((it >> 2) - 1) & 1);
                p1_issue(sb, tmX, tmW, mt, j, it);
            }
            if (lane == 0) DBG_T(0, 5);
            const int head = b >> 2, qq = b & 3;
            const uint8_t* gk = g_img + (size_t)(32 + head) * UNIT_BYTES;
            mbar_wait(bar_staged, 0);
            if (lane < 4) spin_cnt(g_cnt + 32 * (lane < 3 ? (32 * lane + head) / 12 : 8), (lane < 3 ? 128u : 4u) * tag);
            __syncwarp();
            fence_proxy_async_global();
            if (lane == 0) DBG_T(1, 1);
            mbar_expect_tx_e(sb + B2_Q, 12288);
            bulk_g2s_e(sb + SM_Q, g_img + (size_t)head * UNIT_BYTES + qq * 24576, 12288, sb + B2_Q);
            mbar_wait(sb + B1_END, 0);
            mbar_expect_tx_e(sb + B2_KV, KG1 * 12288);
            bulk_g2s_e(sb, gk, KG1 * 6144, sb + B2_KV);
            bulk_g2s_e(sb + 98304, gk + (size_t)32 * UNIT_BYTES, KG1 * 6144, sb + B2_KV);
            if (lane == 0) DBG_T(1, 6);
        }
        mbar_wait(sb + B1_END, 0);
        reg_inc<128>();
    } else if (wgi == 3) {
        reg_dec<104>();
        const int h = warp - 12, r = tid - 384;
        float a[8];
        #pragma unroll
        for (int e = 0; e < 8; e++) a[e] = 0.f;
        const int cgp = b % 30, kq = b / 30;
        if (HELP_WAIT) mbar_wait(bar_full, 0);
        if (b < 120) {
            const uint4* wp = (const uint4*)(wqkv + (size_t)(160 * kq + (r >> 3)) * (3 * DM) + 64 * cgp) + (r & 7);
            uint4 w[10];
            #pragma unroll
            for (int m = 0; m < 10; m++) w[m] = __ldg(wp + (size_t)m * 16 * (3 * DM / 8));
            #pragma unroll
            for (int m = 0; m < 10; m++) {
                a[0] += bf_lo(w[m].x); a[1] += bf_hi(w[m].x); a[2] += bf_lo(w[m].y); a[3] += bf_hi(w[m].y);
                a[4] += bf_lo(w[m].z); a[5] += bf_hi(w[m].z); a[6] += bf_lo(w[m].w); a[7] += bf_hi(w[m].w);
            }
        }
        if (b < 120) {
            #pragma unroll
            for (int e = 0; e < 8; e++) { a[e] += __shfl_xor_sync(0xffffffff, a[e], 8); a[e] += __shfl_xor_sync(0xffffffff, a[e], 16); }
            if (lane < 8) {
                #pragma unroll
                for (int e = 0; e < 8; e++) sts32(s_red + (h * 64 + lane * 8 + e) * 4, __float_as_uint(a[e]));
            }
            bar_sync(4, 128);
            if (r < 64) {
                float s = 0.f;
                #pragma unroll
                for (int w = 0; w < 4; w++) { float v; asm volatile("ld.shared.f32 %0, [%1];" : "=f"(v) : "r"(s_red + (w * 64 + r) * 4)); s += v; }
                st_ll(g_p1_col + kq * (3 * DM) + 64 * cgp + r, __float_as_uint(s), tag);
            }
        }
        #pragma unroll
        for (int i = 0; i < 4; i++) g_ll[b * 512 + i * 128 + r] = make_uint4(0, 0, 0, 0);
        mbar_wait(bar_go, 0);
        if (tid == 384) DBG_T(0, 2);
        if (r < 120) {
            const uint64_t* p = g_p1_col + 240 * j + 2 * r;
            uint64_t v[8];
            for (uint32_t n = 0;; n++) {
                bool ok = true;
                #pragma unroll
                for (int q = 0; q < 4; q++) { ld_ll2(v[2 * q], v[2 * q + 1], p + q * (3 * DM)); ok = ok && (uint32_t)(v[2 * q] >> 32) == tag && (uint32_t)(v[2 * q + 1] >> 32) == tag; }
                if (ok) break;
                if (n > SPIN_LIM) break;
                __nanosleep(100);
            }
            const float c0 = (__uint_as_float((uint32_t)v[0]) + __uint_as_float((uint32_t)v[2])) + (__uint_as_float((uint32_t)v[4]) + __uint_as_float((uint32_t)v[6]));
            const float c1 = (__uint_as_float((uint32_t)v[1]) + __uint_as_float((uint32_t)v[3])) + (__uint_as_float((uint32_t)v[5]) + __uint_as_float((uint32_t)v[7]));
            sts64(s_cs + 8 * r, __float_as_uint(c0), __float_as_uint(c1));
        }
        if (tid == 384) DBG_T(0, 4);
        mbar_wait(bar_free, 0);
        {
            const bool poly = (POLY_MASK >> ((r >> 3) & 15)) & 1;
            #pragma unroll
            for (int ul = 0; ul < 12; ul++) {
                const int u = 12 * j + ul;
                uint32_t v0 = 0, v1 = 0;
                if (u >= 64) v0 = 0x00003F80u;
                else if (u >= 32 && poly) { v0 = 0x42FE4780u; v1 = 0x00003B80u; }
                sts64(sb + P1_STG + ul * 6144 + (r >> 3) * 384 + 256 + (r & 7) * 16 + 8, v0, v1);
            }
        }
        fence_proxy_async();
        mbar_arrive(bar_ready);
        if (tid == 384) DBG_T(0, 6);
        if (j >= 2 && j <= 5) {
            #pragma unroll 1
            for (int gq = 0; gq < 3; gq++) {
                mbar_wait(bar_staged + 8 * gq, 0);
                uint32_t mx[4];
                #pragma unroll
                for (int i = 0; i < 4; i++) {
                    const uint32_t a = sb + P1_STG + (4 * gq + i) * 6144 + (r >> 3) * 384 + (r & 7) * 16;
                    const uint4 v0 = lds128(a), v1 = lds128(a + 128), v2 = lds128(a + 256);
                    const uint32_t w[10] = {v0.x, v0.y, v0.z, v0.w, v1.x, v1.y, v1.z, v1.w, v2.x, v2.y};
                    float m = 0.f, m2 = 0.f;
                    #pragma unroll
                    for (int e = 0; e < 10; e++) { const float lo = bf_lo(w[e]), hi = bf_hi(w[e]); m = fmaf(lo, lo, m); m2 = fmaf(hi, hi, m2); }
                    m += m2;
                    mx[i] = (m == m) ? __float_as_uint(m) : 0x7f800000u;
                }
                #pragma unroll
                for (int i = 0; i < 4; i++) {
                    const uint32_t m = __reduce_max_sync(0xffffffff, mx[i]);
                    const int u = 12 * j + 4 * gq + i;
                    if (lane == 0 && u >= 32 && u < 64) g_kmax[(u - 32) * 64 + mt * 4 + h] = __uint_as_float(m);
                }
            }
        }
        __syncwarp();
        asm volatile("{.reg .pred p; elect.sync _|p, 0xffffffff; @p red.release.gpu.global.add.u32 [%0], 1;}" :: "l"(g_cnt + 32 * 10) : "memory");
        if (tid == 384) DBG_T(0, 10);
        if (lane == 0) mbar_arrive(sb + B1_END);
        mbar_wait(sb + B1_END, 0);
        reg_inc<128>();
        if (tid == 384) {
            spin_cnt(g_cnt + 32 * 10, 512u * tag);
            fence_proxy_async_global();
            mbar_expect_tx(sb + B2_KM, 256);
            bulk_g2s(sb + SM_KM, g_kmax + (b >> 2) * 64, 256, sb + B2_KM);
        }
        __syncwarp();
    } else {
        reg_inc<176>();
        const int wg = (warp >> 2) - 1, wq = warp & 3, g = lane >> 2, t = lane & 3;
        float acc0[64], acc1[56];
        #pragma unroll
        for (int i = 0; i < 64; i++) acc0[i] = 0.f;
        #pragma unroll
        for (int i = 0; i < 56; i++) acc1[i] = 0.f;
        float s0 = 0.f, q0 = 0.f, s1 = 0.f, q1 = 0.f;
        const uint32_t offA = wg * 8192 + (16 * wq + (lane & 15)) * 128, xa = lane & 7, ch = lane >> 4;
        uint32_t A[2][8];
        auto stats = [&](const uint32_t* a) {
            #pragma unroll
            for (int e = 0; e < 8; e += 2) {
                const float l0 = bf_lo(a[e]), h0 = bf_hi(a[e]), l1 = bf_lo(a[e + 1]), h1 = bf_hi(a[e + 1]);
                s0 += l0 + h0; q0 = fmaf(l0, l0, q0); q0 = fmaf(h0, h0, q0);
                s1 += l1 + h1; q1 = fmaf(l1, l1, q1); q1 = fmaf(h1, h1, q1);
            }
        };
        #pragma unroll 1
        for (int it = 0; it < 10; it++) {
            const int s = it & 3;
            mbar_wait(bar_full + 8 * s, (it >> 2) & 1);
            const uint32_t st = sb + s * P1_STAGE;
            const uint64_t db = mkdesc(st + 16384, 8192, 1024, 1);
            #pragma unroll
            for (int hf = 0; hf < 2; hf++) {
                ldsm4(&A[hf][0], st + offA + (((4 * hf + ch) ^ xa) << 4));
                ldsm4(&A[hf][4], st + offA + (((4 * hf + 2 + ch) ^ xa) << 4));
                wg_fence();
                #pragma unroll
                for (int k2 = 0; k2 < 2; k2++) {
                    const uint64_t d = db + (2 * hf + k2) * 128;
                    wg_rs128t<1>(acc0, A[hf][4 * k2], A[hf][4 * k2 + 1], A[hf][4 * k2 + 2], A[hf][4 * k2 + 3], d);
                    wg_rs112t<1>(acc1, A[hf][4 * k2], A[hf][4 * k2 + 1], A[hf][4 * k2 + 2], A[hf][4 * k2 + 3], d + 1024);
                }
                wg_commit();
                stats(A[hf]);
                wg_wait<1>();
                if (hf == 0 && it >= 1 && (tid & 127) == 0) {
                    mbar_arrive(bar_empty + 8 * ((it - 1) & 3));
                    if (it == 1) mbar_arrive(bar_go);
                    if (it == 8) mbar_arrive(bar_free);
                }
            }
        }
        #pragma unroll
        for (int o = 1; o <= 2; o <<= 1) {
            s0 += __shfl_xor_sync(0xffffffff, s0, o); q0 += __shfl_xor_sync(0xffffffff, q0, o);
            s1 += __shfl_xor_sync(0xffffffff, s1, o); q1 += __shfl_xor_sync(0xffffffff, q1, o);
        }
        const float mu0 = s0 * (1.f / DM), mu1 = s1 * (1.f / DM);
        const float rs0 = rsqrtf(fmaxf(q0 * (1.f / DM) - mu0 * mu0, 0.f) + 1e-5f), rs1 = rsqrtf(fmaxf(q1 * (1.f / DM) - mu1 * mu1, 0.f) + 1e-5f);
        wg_wait<0>();
        fence_f(acc0); fence_f(acc1);
        DBG_R(d7);
        mbar_wait(bar_ready, 0);
        DBG_R(d11);
        constexpr int PF = 5;
        float c0[30], c1[30];
        #pragma unroll
        for (int bb = 0; bb < PF; bb++) asm volatile("ld.shared.v2.f32 {%0,%1}, [%2];" : "=f"(c0[bb]), "=f"(c1[bb]) : "r"(s_cs + 4 * (8 * bb + 2 * t)));
        const int nq = min(max((640 - 240 * j) / 8, 0), 30);
        const int th = t >> 1;
        const uint32_t base = sb + P1_STG + (8 * wg + 2 * wq) * 384 + g * 16 + (t & 1) * 4;
        const uint32_t b8 = base + th * 8, b120 = base + th * 120, b5888 = base + th * 5888;
        uint8_t* gdst = g_img + (size_t)(12 * j) * UNIT_BYTES + mt * 6144 + wg * 3072;
        #pragma unroll
        for (int bb = 0; bb < 30; bb++) {
            if (bb + PF < 30) asm volatile("ld.shared.v2.f32 {%0,%1}, [%2];" : "=f"(c0[bb + PF]), "=f"(c1[bb + PF]) : "r"(s_cs + 4 * (8 * (bb + PF) + 2 * t)));
            const float* ac = bb < 16 ? &acc0[4 * bb] : &acc1[4 * (bb - 16)];
            const float fq = (bb / 10) * 10 < nq ? QSCALE : 1.f;
            const float f0 = rs0 * fq, f1 = rs1 * fq;
            const float v0 = (ac[0] - mu0 * c0[bb]) * f0, v1 = (ac[1] - mu0 * c1[bb]) * f0;
            const float v2 = (ac[2] - mu1 * c0[bb]) * f1, v3 = (ac[3] - mu1 * c1[bb]) * f1;
            const int q = 2 * bb, dq = q % 5;
            const uint32_t offA = (q / 5) * 6144 + (dq / 2) * 128 + (dq % 2) * 8;
            const uint32_t ad = ((dq == 4) ? b5888 : ((dq & 1) ? b120 : b8)) + offA;
            sts32(ad, pack_bf16(v0, v1));
            sts32(ad + 384, pack_bf16(v2, v3));
            if (bb % EPI_B == EPI_B - 1) {
                fence_proxy_async();
                __syncwarp();
                #pragma unroll
                for (int ul = (bb + 1 - EPI_B) / 5 * 2; ul < (bb + 1) / 5 * 2; ul++)
                    bulk_s2g_e(gdst + (size_t)ul * UNIT_BYTES + wq * 768, sb + P1_STG + ul * 6144 + wg * 3072 + wq * 768, 768);
            }
            if (bb % 10 == 9) { __syncwarp(); if (lane == 0) mbar_arrive(bar_staged + 8 * (bb / 10)); }
        }
        DBG_R(d8);
        asm volatile("{.reg .pred p; elect.sync _|p, 0xffffffff; @p cp.async.bulk.commit_group; @p cp.async.bulk.wait_group 0; @p red.relaxed.gpu.global.add.u32 [%0], 1;}" :: "l"(cnt) : "memory");
        if (tid == 128) { DBG_T(0, 9); DBG_W(0, 7, d7); DBG_W(0, 11, d11); DBG_W(0, 8, d8); }
        reg_dec<128>();
        if (lane == 0) mbar_arrive(sb + B1_END);
        mbar_wait(sb + B1_END, 0);
    }
}

constexpr float SAFE_BOUND2 = 9800.f;

__device__ __forceinline__ uint32_t exp2_bf16x2(float t0, float t1, uint32_t k1, uint32_t k2) {
    uint32_t u, z, p, r;
    asm("prmt.b32 %0, %1, %2, 0x5410;" : "=r"(u) : "r"(__float_as_uint(t0)), "r"(__float_as_uint(t1)));
    asm("lop3.b32 %0, %1, 0x007F007F, %2, 0xEA;" : "=r"(z) : "r"(u), "r"(k1));
    asm("fma.rn.bf16x2 %0, %1, %2, %3;" : "=r"(p) : "r"(z), "r"(k2), "r"(0xBC99BC99u));
    asm("fma.rn.bf16x2 %0, %1, %2, %3;" : "=r"(p) : "r"(p), "r"(z), "r"(0x3F303F30u));
    asm("lop3.b32 %0, %1, %2, 0xFF80FF80, 0xE4;" : "=r"(r) : "r"(u), "r"(p));
    return r;
}
template<uint32_t MASK>
__device__ __forceinline__ void exp_step(const float (&s)[32], uint32_t (&p)[16], uint32_t k1, uint32_t k2) {
    #pragma unroll
    for (int b = 0; b < 8; b++) {
        if ((MASK >> b) & 1) { p[2 * b] = exp2_bf16x2(s[4 * b], s[4 * b + 1], k1, k2); p[2 * b + 1] = exp2_bf16x2(s[4 * b + 2], s[4 * b + 3], k1, k2); }
        else { p[2 * b] = pack_bf16(ex2f(s[4 * b]), ex2f(s[4 * b + 1])); p[2 * b + 1] = pack_bf16(ex2f(s[4 * b + 2]), ex2f(s[4 * b + 3])); }
    }
}
#define DADV 384
#define VOFF 98304
#define DESC_ADV(d) asm volatile("{.reg .b32 lo, hi; mov.b64 {lo, hi}, %0; add.u32 lo, lo, 384; mov.b64 %0, {lo, hi};}" : "+l"(d))
__device__ __forceinline__ uint64_t desc_pack(uint32_t lo, uint32_t hi) { uint64_t d; asm("mov.b64 %0, {%1, %2};" : "=l"(d) : "r"(lo), "r"(hi)); return d; }

__device__ __forceinline__ void mid_signal(const uint32_t sb, const uint8_t* src, unsigned* flag) {
    asm volatile("{\n.reg .pred e, p, q;\n.reg .b32 old, old2;\n"
        "elect.sync _|e, 0xffffffff;\n"
        "mov.b32 old, 1;\n"
        "mov.b32 old2, 1;\n"
        "@e atom.acq_rel.cta.shared::cta.add.u32 old, [%0], 1;\n"
        "setp.eq.and.u32 p, old, 15, e;\n"
        "@p fence.proxy.async.global;\n"
        "@p mbarrier.arrive.expect_tx.shared::cta.b64 _, [%1], 102400;\n"
        "@p cp.async.bulk.shared::cluster.global.mbarrier::complete_tx::bytes [%2], [%5], 25600, [%1];\n"
        "@p cp.async.bulk.shared::cluster.global.mbarrier::complete_tx::bytes [%3], [%6], 38400, [%1];\n"
        "@p cp.async.bulk.shared::cluster.global.mbarrier::complete_tx::bytes [%4], [%7], 38400, [%1];\n"
        "setp.eq.and.u32 p, old, 0, e;\n"
        "setp.ne.u32 q, old, old;\n"
        "@p mbarrier.test_wait.parity.shared::cta.b64 q, [%8], 0;\n"
        "@q atom.relaxed.cta.shared::cta.add.u32 old2, [%9], 1;\n"
        "setp.eq.and.u32 q, old2, 0, q;\n"
        "@q fence.acq_rel.gpu;\n"
        "@q red.relaxed.gpu.global.add.u32 [%10], 1;\n"
        "@q red.relaxed.gpu.global.add.u32 [%10 + 2048], 1;\n"
        "@q red.relaxed.gpu.global.add.u32 [%10 + 4096], 1;\n"
        "@q red.relaxed.gpu.global.add.u32 [%10 + 6144], 1;\n"
        "}" :: "r"(sb + B2_MID), "r"(sb + B3_B), "r"(sb + SM_Q), "r"(sb), "r"(sb + 98304), "l"(src), "l"(src + 25600), "l"(src + 64000),
               "r"(sb + B2_T0), "r"(sb + B2_FIRST), "l"(flag) : "memory");
}
__device__ __forceinline__ void attn_fast(float (&o)[12], const uint32_t (&qa)[4], const uint32_t (&qb)[4], uint64_t dK0, uint64_t dK1, uint64_t dV, uint32_t bars,
                                          uint32_t k1, uint32_t k2, const uint32_t (&hi)[12], const uint32_t sb, const uint8_t* wo_src, unsigned* flag, const bool mid) {
    float s[32]; uint32_t p[16];
    mbar_wait(bars, 0);
    wg_fence();
    wg_rs64<0>(s, qa[0], qa[1], qa[2], qa[3], dK0);
    wg_rs64<1>(s, qb[0], qb[1], qb[2], qb[3], dK1);
    wg_commit();
    const uint32_t lK0 = (uint32_t)dK0, lK1 = (uint32_t)dK1, lV = (uint32_t)dV;
    uint64_t a0 = desc_pack(lK0 + 192 - DADV, hi[0]), a1 = desc_pack(lK1 + 192 - DADV, hi[1]);
    uint64_t b0 = desc_pack(lK0, hi[2]), b1 = desc_pack(lK1, hi[3]);
    uint64_t v0 = desc_pack(lV - DADV, hi[4]), v1 = desc_pack(lV + 48 - DADV, hi[5]), v2 = desc_pack(lV + 96 - DADV, hi[6]), v3 = desc_pack(lV + 144 - DADV, hi[7]);
    uint64_t w0 = desc_pack(lV + 192 - DADV, hi[8]), w1 = desc_pack(lV + 240 - DADV, hi[9]), w2 = desc_pack(lV + 288 - DADV, hi[10]), w3 = desc_pack(lV + 336 - DADV, hi[11]);
    uint32_t bar = bars + 8;
    #pragma unroll 1
    for (int hf = mid ? 0 : 1; hf < 2; hf++) {
    #pragma unroll 1
    for (int jo = mid ? 8 : 16; jo > 0; jo--) {
        wg_wait<0>(); fence_f(s); fence_f(o);
        DESC_ADV(a0); DESC_ADV(a1); DESC_ADV(v0); DESC_ADV(v1); DESC_ADV(v2); DESC_ADV(v3);
        exp_step<POLY_MASK & 0xFF>(s, p, k1, k2);
        fence_u(p);
        wg_fence();
        wg_pv24<1>(o, p[0], p[1], p[2], p[3], v0); wg_pv24<1>(o, p[4], p[5], p[6], p[7], v1);
        wg_pv24<1>(o, p[8], p[9], p[10], p[11], v2); wg_pv24<1>(o, p[12], p[13], p[14], p[15], v3);
        wg_rs64<0>(s, qa[0], qa[1], qa[2], qa[3], a0);
        wg_rs64<1>(s, qb[0], qb[1], qb[2], qb[3], a1);
        wg_commit();
        wg_wait<0>(); fence_f(s); fence_f(o);
        DESC_ADV(b0); DESC_ADV(b1); DESC_ADV(w0); DESC_ADV(w1); DESC_ADV(w2); DESC_ADV(w3);
        exp_step<(POLY_MASK >> 8) & 0xFF>(s, p, k1, k2);
        mbar_wait(bar, 0);
        bar += 8;
        fence_u(p);
        wg_fence();
        wg_pv24<1>(o, p[0], p[1], p[2], p[3], w0); wg_pv24<1>(o, p[4], p[5], p[6], p[7], w1);
        wg_pv24<1>(o, p[8], p[9], p[10], p[11], w2); wg_pv24<1>(o, p[12], p[13], p[14], p[15], w3);
        wg_rs64<0>(s, qa[0], qa[1], qa[2], qa[3], b0);
        wg_rs64<1>(s, qb[0], qb[1], qb[2], qb[3], b1);
        wg_commit();
    }
    wg_wait<0>(); fence_f(o); fence_f(s);
    if (mid && hf == 0) mid_signal(sb, wo_src, flag);
    }
}

__device__ __forceinline__ void attn_safe(float (&o)[12], const uint32_t (&qin)[6], uint64_t dK0, uint64_t dK1, uint64_t dV, uint32_t bars, int t) {
    float s[32]; uint32_t p[16];
    uint32_t q4 = (t < 2) ? qin[4] : 0u, q5 = (t < 2) ? qin[5] : 0u;
    uint32_t zz = 0; asm volatile("" : "+r"(zz));
    float m0 = -INFINITY, m1 = -INFINITY;
    #pragma unroll 1
    for (int jj = 0; jj < 32; jj++) {
        mbar_wait(bars + 8 * (jj >> 1), 0);
        const uint64_t off = (uint64_t)(jj * 192);
        wg_fence();
        wg_rs64<0>(s, qin[0], qin[1], qin[2], qin[3], dK0 + off);
        wg_rs64<1>(s, q4, q5, zz, zz, dK1 + off);
        wg_commit();
        wg_wait<0>(); fence_f(s); fence_f(o);
        float a0 = m0, a1 = m1;
        #pragma unroll
        for (int b = 0; b < 8; b++) { a0 = fmaxf(a0, fmaxf(s[4 * b], s[4 * b + 1])); a1 = fmaxf(a1, fmaxf(s[4 * b + 2], s[4 * b + 3])); }
        a0 = fmaxf(a0, __shfl_xor_sync(0xffffffff, a0, 1)); a0 = fmaxf(a0, __shfl_xor_sync(0xffffffff, a0, 2));
        a1 = fmaxf(a1, __shfl_xor_sync(0xffffffff, a1, 1)); a1 = fmaxf(a1, __shfl_xor_sync(0xffffffff, a1, 2));
        const float c0 = (m0 == a0) ? 1.f : ex2f(m0 - a0), c1 = (m1 == a1) ? 1.f : ex2f(m1 - a1);
        m0 = a0; m1 = a1;
        #pragma unroll
        for (int b = 0; b < 3; b++) { o[4 * b] *= c0; o[4 * b + 1] *= c0; o[4 * b + 2] *= c1; o[4 * b + 3] *= c1; }
        #pragma unroll
        for (int b = 0; b < 8; b++) {
            p[2 * b] = pack_bf16(ex2f(s[4 * b] - m0), ex2f(s[4 * b + 1] - m0));
            p[2 * b + 1] = pack_bf16(ex2f(s[4 * b + 2] - m1), ex2f(s[4 * b + 3] - m1));
        }
        fence_u(p); fence_f(o);
        wg_fence();
        #pragma unroll
        for (int k = 0; k < 4; k++) wg_pv24<1>(o, p[4 * k], p[4 * k + 1], p[4 * k + 2], p[4 * k + 3], dV + off + (uint64_t)(k * 48));
        wg_commit();
        wg_wait<0>(); fence_f(o);
    }
}

__device__ __forceinline__ void p2_init(const uint32_t sb) {
    for (int i = 0; i < 17; i++) mbar_init(sb + B2_KV + 8 * i, 1);
    mbar_init(sb + B2_DONE, 16); mbar_init(sb + B2_Q, 1); mbar_init(sb + B2_Q + 8, 1);
    mbar_init(sb + B2_T0, 4); mbar_init(sb + B2_KM, 1);
    sts32(sb + B2_MID, 0); sts32(sb + B2_FIRST, 0);
    for (int i = 0; i < 4; i++) sts32(sb + B2_GRP + 4 * i, 0);
    for (int i = 0; i < 16; i++) asm volatile("st.shared.u32 [%0], %1;" :: "r"(sb + B2_HI + i * 4), "r"(i < 4 ? 24u : 8u) : "memory");
    asm volatile("st.shared.v4.u32 [%0], {%1,%1,%2,%3};" :: "r"(sb + B2_CONST), "r"(0u), "r"(0x3F803F80u), "r"(0x3EAC3EACu) : "memory");
    for (int i = 0; i < 17; i++) if (i != 0 && i != KG1 && i != KG2 && !(i == KG3 && KG3 < 16)) mbar_arrive(sb + B2_KV + 8 * i);
}

__device__ __forceinline__ void p2_phase(const uint32_t sb, const int tid, const int warp, const int lane, const int bid) {
    const uint32_t bars = sb + B2_KV;
    const int head = bid >> 2, qq = bid & 3;
    const int wg = warp >> 2, wq = warp & 3, g = lane >> 2, t = lane & 3;
    if (tid == 0) DBG_T(1, 0);

    const uint64_t dK0 = mkdesc(sb, 128, 384, 0), dK1 = mkdesc(sb + 256, 0, 384, 0), dV = mkdesc(sb + VOFF, 384, 128, 0);
    uint32_t hi[12];
    {
        uint32_t hv;
        asm volatile("ld.volatile.shared.u32 %0, [%1];" : "=r"(hv) : "r"(sb + B2_HI + (lane & 15) * 4));
        #pragma unroll
        for (int i = 0; i < 12; i++) hi[i] = __shfl_sync(0xffffffff, hv, i);
    }
    uint32_t z0, z1, k1, k2;
    asm volatile("ld.volatile.shared.v4.u32 {%0,%1,%2,%3}, [%4];" : "=r"(z0), "=r"(z1), "=r"(k1), "=r"(k2) : "r"(sb + B2_CONST));
    auto load_q = [&](uint32_t (&q)[6], int tl) {
        const uint32_t qa = sb + SM_Q + (((tl * 4 + wg) * 64 + wq * 16) >> 3) * 384 + g * 16 + t * 4;
        q[0] = lds32(qa); q[1] = lds32(qa + 384); q[2] = lds32(qa + 128); q[3] = lds32(qa + 384 + 128); q[4] = lds32(qa + 256); q[5] = lds32(qa + 384 + 256);
        if (t >= 2) q[4] = q[5] = (t == 2 ? 0x3F803F80u : 0x00003F80u);
    };
    auto store_o = [&](const float (&o)[12], int tl) {
        const float l0 = __shfl_sync(0xffffffff, o[8], (lane & ~3) | 2), l1 = __shfl_sync(0xffffffff, o[10], (lane & ~3) | 2);
        const float i0 = 1.f / l0, i1 = 1.f / l1;
        uint8_t* op = g_O + (size_t)((((qq * 4 + wg) * 2 + tl) * 8 + (head >> 2)) * 4 + wq) * 2560 + (head & 3) * 640;
        *(uint4*)(op + lane * 16) = make_uint4(pack_bf16(o[0] * i0, o[1] * i0), pack_bf16(o[2] * i1, o[3] * i1), pack_bf16(o[4] * i0, o[5] * i0), pack_bf16(o[6] * i1, o[7] * i1));
        if (t < 2) *(uint2*)(op + 512 + (2 * g + t) * 8) = make_uint2(pack_bf16(o[8] * i0, o[9] * i0), pack_bf16(o[10] * i1, o[11] * i1));
    };
    auto norm_q = [&](const uint32_t (&q)[6]) {
        float n0 = 0.f, n1 = 0.f, a;
        a = bf_lo(q[0]); n0 = fmaf(a, a, n0); a = bf_hi(q[0]); n0 = fmaf(a, a, n0);
        a = bf_lo(q[2]); n0 = fmaf(a, a, n0); a = bf_hi(q[2]); n0 = fmaf(a, a, n0);
        a = bf_lo(q[1]); n1 = fmaf(a, a, n1); a = bf_hi(q[1]); n1 = fmaf(a, a, n1);
        a = bf_lo(q[3]); n1 = fmaf(a, a, n1); a = bf_hi(q[3]); n1 = fmaf(a, a, n1);
        if (t < 2) {
            a = bf_lo(q[4]); n0 = fmaf(a, a, n0); a = bf_hi(q[4]); n0 = fmaf(a, a, n0);
            a = bf_lo(q[5]); n1 = fmaf(a, a, n1); a = bf_hi(q[5]); n1 = fmaf(a, a, n1);
        }
        n0 += __shfl_xor_sync(0xffffffff, n0, 1); n0 += __shfl_xor_sync(0xffffffff, n0, 2);
        n1 += __shfl_xor_sync(0xffffffff, n1, 1); n1 += __shfl_xor_sync(0xffffffff, n1, 2);
        return max(__float_as_uint(n0), __float_as_uint(n1));
    };
    unsigned* const flag = g_cnt + 32 * (16 + (qq * 4 * 8 + (head >> 2)) * 2);
    auto publish0 = [&]() {
        if (lane == 0) {
            uint32_t old;
            asm volatile("atom.relaxed.cta.shared::cta.add.u32 %0, [%1], 1;" : "=r"(old) : "r"(sb + B2_FIRST) : "memory");
            if (old == 0) {
                mbar_wait(sb + B2_T0, 0);
                fence_gpu();
                #pragma unroll
                for (int i = 0; i < 4; i++) red_relaxed(flag + 32 * 16 * i, 1);
            }
        }
        __syncwarp();
    };
    if (warp == 0) kv_issue_rest(sb, head, qq);
    uint32_t nq = 0;
    const uint8_t* wo_src = g_wo + (bid & 7) * 102400;
    bool safe_mode = false;
    #pragma unroll 1
    for (int tl = 0; tl < 2; tl++) {
        uint32_t q[6];
        mbar_wait(sb + B2_Q + 8 * tl, 0);
        load_q(q, tl);
        nq = max(nq, norm_q(q));
        if (tl == 1) {
            uint32_t km0, km1;
            mbar_wait(sb + B2_KM, 0);
            asm volatile("ld.volatile.shared.v2.u32 {%0, %1}, [%2];" : "=r"(km0), "=r"(km1) : "r"(sb + SM_KM + lane * 8) : "memory");
            const float km = __uint_as_float(__reduce_max_sync(0xffffffff, max(km0, km1)));
            const bool bad = !(__uint_as_float(nq) * km <= SAFE_BOUND2);
            uint32_t unsafe;
            asm volatile("{.reg .pred p, r; setp.ne.u32 p, %1, 0; barrier.cta.red.or.aligned.pred r, %2, 128, p; selp.u32 %0, 1, 0, r;}"
                : "=r"(unsafe) : "r"((uint32_t)bad), "r"(1 + wg) : "memory");
            unsafe = __shfl_sync(0xffffffff, unsafe, 0);
            if (__builtin_expect(unsafe, 0)) { safe_mode = true; break; }
            if ((tid & 127) == 0) mbar_arrive(sb + B2_T0);
        }
        fence_u(q);
        float o[12];
        #pragma unroll
        for (int i = 0; i < 12; i++) o[i] = 0.f;
        fence_f(o);
        if (tid == 0) DBG_T(1, 2 + 2 * tl);
        {
            const uint32_t qa[4] = {q[0], q[1], q[2], q[3]}, qb[4] = {q[4], q[5], z0, z1};
            attn_fast(o, qa, qb, dK0, dK1, dV, bars, k1, k2, hi, sb, wo_src, flag, tl == 1);
        }
        if (tid == 0) DBG_T(1, 3 + 2 * tl);
        store_o(o, tl);
        if (tid == 0 && tl == 0) DBG_T(1, 7);
    }
    if (__builtin_expect(safe_mode, 0)) {
        #pragma unroll 1
        for (int tl = 0; tl < 2; tl++) {
            uint32_t q[6];
            float o[12];
            load_q(q, tl);
            #pragma unroll
            for (int i = 0; i < 12; i++) o[i] = 0.f;
            fence_u(q); fence_f(o);
            attn_safe(o, q, dK0, dK1, dV, bars, t);
            store_o(o, tl);
            if (tl == 0) { bar_sync(1 + wg, 128); if ((tid & 127) == 0) mbar_arrive(sb + B2_T0); }
        }
        mid_signal(sb, wo_src, flag);
        publish0();
    }
    else publish0();
    __syncwarp();
    if (lane == 0) {
        uint32_t old;
        asm volatile("atom.acq_rel.cta.shared::cta.add.u32 %0, [%1], 1;" : "=r"(old) : "r"(sb + B2_GRP + 4 * wg) : "memory");
        if (old == 3) { fence_gpu(); red_relaxed(flag + 32 * 16 * wg + 32, 1); }
    }
    __syncwarp();
    if (lane == 0) mbar_arrive(sb + B2_DONE);
}

constexpr int P3_SLOT = 10240;
__host__ __device__ constexpr uint32_t p3_slot(int i) { return (i < 5 ? 38400 : 136704 - 5 * P3_SLOT) + i * P3_SLOT; }
__host__ __device__ constexpr uint32_t p3_wo(int it) { return (it < 2 ? SM_Q : it < 5 ? -2 * 12800 : 98304 - 5 * 12800) + it * 12800; }
constexpr int P3_WG = 38400;
constexpr int P3_WU = P3_WG + 20480;
constexpr int P3_WD = 136704 + 3 * P3_SLOT;
constexpr int P3_OST = 0;
constexpr int P3_KEYS = SM_KEYS;
constexpr int P3_XS = SM_BUF;
constexpr int P3_RED = P3_XS + 2560;
constexpr int P3_ACT = P3_RED + 2048;

__device__ __forceinline__ void cp_async16(uint32_t dst, const void* src) { asm volatile("cp.async.cg.shared.global [%0], [%1], 16;" :: "r"(dst), "l"(src) : "memory"); }
__device__ __forceinline__ void ldsm_x4_t(uint32_t& r0, uint32_t& r1, uint32_t& r2, uint32_t& r3, uint32_t a) {
    asm volatile("ldmatrix.sync.aligned.m8n8.x4.trans.shared.b16 {%0,%1,%2,%3}, [%4];" : "=r"(r0), "=r"(r1), "=r"(r2), "=r"(r3) : "r"(a) : "memory");
}
__device__ __forceinline__ void mma16816(float (&d)[4], uint32_t a0, uint32_t a2, uint32_t b0, uint32_t b1) {
    asm volatile("mma.sync.aligned.m16n8k16.row.col.f32.bf16.bf16.f32 {%0,%1,%2,%3}, {%4,%5,%6,%7}, {%8,%9}, {%0,%1,%2,%3};"
        : "+f"(d[0]), "+f"(d[1]), "+f"(d[2]), "+f"(d[3]) : "r"(a0), "r"(0u), "r"(a2), "r"(0u), "r"(b0), "r"(b1));
}
__device__ __forceinline__ float ldsf(uint32_t a) { float v; asm volatile("ld.shared.f32 %0, [%1];" : "=f"(v) : "r"(a) : "memory"); return v; }
__device__ __forceinline__ void stsf(uint32_t a, float v) { asm volatile("st.shared.f32 [%0], %1;" :: "r"(a), "f"(v) : "memory"); }
__device__ __forceinline__ void bar_arrive(int id, int n) { asm volatile("bar.arrive %0, %1;" :: "r"(id), "r"(n) : "memory"); }

__device__ __forceinline__ uint2 lds64(uint32_t a) { uint2 v; asm volatile("ld.shared.v2.u32 {%0,%1}, [%2];" : "=r"(v.x), "=r"(v.y) : "r"(a) : "memory"); return v; }
__device__ __forceinline__ unsigned ld_relaxed(const unsigned* p) { unsigned v; asm volatile("ld.relaxed.gpu.global.u32 %0, [%1];" : "=r"(v) : "l"(p) : "memory"); return v; }

template<int HF> __device__ __forceinline__ void p3_gemm(float (&acc)[40], const uint32_t sb, const int wq, const int lane) {
    const uint32_t am = sb + wq * 2560 + lane * 16, at = sb + wq * 2560 + ((lane & 3) >> 1) * 640 + 512 + (2 * (lane >> 2) + (lane & 1)) * 8;
    const uint32_t bar_full = sb + B3_FULL, bar_empty = sb + B3_EMPTY;
    const uint64_t d0 = mkdesc(sb, 1280, 128, 0);
    uint32_t A[2][20];
    auto load_a = [&](uint32_t (&a)[20], const int it) {
        const uint32_t so = p3_slot(HF ? (it < 2 ? 8 + it : it - 2) : it);
        mbar_wait(bar_full + 8 * (8 * HF + it), 0);
        #pragma unroll
        for (int i = 0; i < 4; i++) { const uint4 m = lds128(am + so + 640 * i); a[4 * i] = m.x; a[4 * i + 1] = m.y; a[4 * i + 2] = m.z; a[4 * i + 3] = m.w; }
        const uint2 t0 = lds64(at + so), t1 = lds64(at + so + 1280);
        a[16] = t0.x; a[17] = t0.y; a[18] = t1.x; a[19] = t1.y;
    };
    fence_f(acc);
    load_a(A[0], 0);
    #pragma unroll
    for (int it = 0; it < 8; it++) {
        wg_fence();
        #pragma unroll
        for (int i = 0; i < 5; i++) wg_rs80t<1>(acc, A[it & 1][4 * i], A[it & 1][4 * i + 1], A[it & 1][4 * i + 2], A[it & 1][4 * i + 3], d0 + ((p3_wo(it) >> 4) + 160 * i));
        wg_commit();
        const int e = HF ? (it == 1 ? 6 : it == 5 ? 7 : -1) : (it < 6 ? it : -1);
        if (e >= 0) asm volatile("{.reg .pred p; elect.sync _|p, 0xffffffff; @p mbarrier.arrive.shared::cta.b64 _, [%0];}" :: "r"(bar_empty + 8 * e) : "memory");
        if (it < 7) { wg_wait<1>(); load_a(A[(it + 1) & 1], it + 1); }
    }
    wg_wait<0>();
}

__device__ __forceinline__ void p3_phase(const uint32_t sb, const int tid, const int warp, const int lane, const int cta,
                                         const bf16* __restrict__ x, const bf16* __restrict__ wr, const bf16* __restrict__ wdown, bf16* __restrict__ out) {
    const int j = cta & 7, mt = cta >> 3;
    const uint32_t bar_full = sb + B3_FULL, bar_empty = sb + B3_EMPTY, bar_b = sb + B3_B, bar_w1 = sb + B3_W1, bar_w2 = sb + B3_W2;
    const uint32_t tag = ld_relaxed(&g_epoch) + 1;
    if (warp >= 8) {
        const int i = warp - 8;
        const uint8_t* src = g_O + (size_t)mt * (16 * P3_SLOT) + i * P3_SLOT;
        const unsigned* fp = g_cnt + 32 * (16 + (mt * 8 + i) * 2);
        if (i == 0) {
            if (lane == 0) DBG_T(2, 0);
            if (lane < 8) spin_cnt(g_cnt + 32 * (16 + (mt * 8 + lane) * 2), 4u * tag);
            __syncwarp();
        }
        if (lane == 0) {
            mbar_wait(sb + B2_DONE, 0);
            if (i == 0) {
                DBG_T(2, 1);
                fence_proxy_async_global();
                #pragma unroll
                for (int s = 0; s < 8; s++) {
                    mbar_expect_tx(bar_full + 8 * s, P3_SLOT);
                    bulk_g2s(sb + p3_slot(s), src + s * P3_SLOT, P3_SLOT, bar_full + 8 * s);
                }
            }
            if (i == 7) DBG_T(2, 11);
            spin_cnt(fp + 32, 4u * tag);
            if (i == 7) DBG_T(2, 15);
            if (i >= 2) mbar_wait(bar_empty + 8 * (i - 2), 0);
            fence_proxy_async_global();
            mbar_expect_tx(bar_full + 8 * (8 + i), P3_SLOT);
            bulk_g2s(sb + p3_slot(i < 2 ? 8 + i : i - 2), src + 8 * P3_SLOT, P3_SLOT, bar_full + 8 * (8 + i));
            if (i == 7) DBG_T(2, 2);
            if (cta < 96 && i == 5) {
                spin_cnt(g_cnt + 32 * 9, 4u * tag);
                fence_proxy_async_global();
                mbar_wait(bar_empty + 8 * 7, 0);
                mbar_expect_tx(bar_w1, 40960);
                bulk_g2s(sb + P3_WG, g_wgu + (size_t)cta * 40960, 40960, bar_w1);
            }
        }
        if (cta < 96 && i == 1) {
            __syncwarp();
            mbar_wait(bar_empty + 8 * 6, 0);
            mbar_expect_tx_e(bar_w2, 20480);
            __syncwarp();
            if (lane < 16) bulk_g2s(sb + P3_WD + lane * 1296, wdown + (size_t)(16 * cta + lane) * DM, 1280, bar_w2);
        }
        return;
    }
    const int wg = warp >> 2, wq = warp & 3, g = lane >> 2, t = lane & 3;
    const int row = 512 * (mt >> 2) + 256 * wg + 64 * (mt & 3) + 16 * wq + g;

    const int col = 80 * j + 2 * t;
    float acc[40];
    uint32_t wv[10];
    {
        uint32_t hx[20];
        #pragma unroll
        for (int b = 0; b < 10; b++) {
            hx[2 * b] = __ldg((const uint32_t*)(x + (size_t)row * DM + col + 8 * b));
            hx[2 * b + 1] = __ldg((const uint32_t*)(x + (size_t)(row + 8) * DM + col + 8 * b));
            wv[b] = __ldg((const uint32_t*)(wr + col + 8 * b));
        }
        #pragma unroll
        for (int b = 0; b < 10; b++) { acc[4 * b] = bf_lo(hx[2 * b]); acc[4 * b + 1] = bf_hi(hx[2 * b]); acc[4 * b + 2] = bf_lo(hx[2 * b + 1]); acc[4 * b + 3] = bf_hi(hx[2 * b + 1]); }
    }
    float sw = 0.f;
    #pragma unroll
    for (int i = 0; i < 10; i++) { const uint32_t u = __ldg((const uint32_t*)wr + lane + 32 * i); sw += bf_lo(u) + bf_hi(u); }
    #pragma unroll
    for (int o = 16; o; o >>= 1) sw += __shfl_xor_sync(0xffffffff, sw, o);
    if (tid == 0) DBG_T(2, 3);
    mbar_wait(bar_b, 0);
    if (tid == 0) DBG_T(2, 4);
    if (wg == 0) p3_gemm<0>(acc, sb, wq, lane); else p3_gemm<1>(acc, sb, wq, lane);
    fence_f(acc);
    if (tid == 0) DBG_T(2, 5);
    if (tid == 128) DBG_T(2, 10);
    uint32_t hp[20];
    float s0 = 0.f, q0 = 0.f, d0 = 0.f, s1 = 0.f, q1 = 0.f, d1 = 0.f;
    #pragma unroll
    for (int b = 0; b < 10; b++) {
        hp[2 * b] = pack_bf16(acc[4 * b], acc[4 * b + 1]);
        hp[2 * b + 1] = pack_bf16(acc[4 * b + 2], acc[4 * b + 3]);
        const float h0 = bf_lo(hp[2 * b]), h1 = bf_hi(hp[2 * b]), h2 = bf_lo(hp[2 * b + 1]), h3 = bf_hi(hp[2 * b + 1]);
        const float w0 = bf_lo(wv[b]), w1 = bf_hi(wv[b]);
        s0 += h0 + h1; q0 = fmaf(h0, h0, fmaf(h1, h1, q0)); d0 = fmaf(h0, w0, fmaf(h1, w1, d0));
        s1 += h2 + h3; q1 = fmaf(h2, h2, fmaf(h3, h3, q1)); d1 = fmaf(h2, w0, fmaf(h3, w1, d1));
    }
    #pragma unroll
    for (int o = 1; o <= 2; o <<= 1) {
        s0 += __shfl_xor_sync(0xffffffff, s0, o); q0 += __shfl_xor_sync(0xffffffff, q0, o); d0 += __shfl_xor_sync(0xffffffff, d0, o);
        s1 += __shfl_xor_sync(0xffffffff, s1, o); q1 += __shfl_xor_sync(0xffffffff, q1, o); d1 += __shfl_xor_sync(0xffffffff, d1, o);
    }
    const uint32_t stb = (mt * 8 + warp) * 128;
    if (t < 2) st_ll4(g_ll_st + stb + t * 64 + j * 8 + g, __float_as_uint(t ? s1 : s0), __float_as_uint(t ? q1 : q0), __float_as_uint(t ? d1 : d0), tag);
    if (tid == 0) DBG_T(2, 6);
    float mu0, rs0, r0, mu1, rs1, r1;
    {
        const uint4* p = g_ll_st + stb + t * 8 + g;
        constexpr int D1 = 32;
        uint32_t n = 0;
        uint4 v0, v1, v2, v3;
        while (true) {
            v0 = ld_ll4(p); v1 = ld_ll4(p + D1); v2 = ld_ll4(p + 64); v3 = ld_ll4(p + 64 + D1);
            if (__all_sync(0xffffffff, v0.w == tag && v1.w == tag && v2.w == tag && v3.w == tag)) break;
            if (++n > SPIN_LIM) break;
        }
        s0 = __uint_as_float(v0.x) + __uint_as_float(v1.x); q0 = __uint_as_float(v0.y) + __uint_as_float(v1.y); d0 = __uint_as_float(v0.z) + __uint_as_float(v1.z);
        s1 = __uint_as_float(v2.x) + __uint_as_float(v3.x); q1 = __uint_as_float(v2.y) + __uint_as_float(v3.y); d1 = __uint_as_float(v2.z) + __uint_as_float(v3.z);
        #pragma unroll
        for (int o = 1; o <= 2; o <<= 1) {
            s0 += __shfl_xor_sync(0xffffffff, s0, o); q0 += __shfl_xor_sync(0xffffffff, q0, o); d0 += __shfl_xor_sync(0xffffffff, d0, o);
            s1 += __shfl_xor_sync(0xffffffff, s1, o); q1 += __shfl_xor_sync(0xffffffff, q1, o); d1 += __shfl_xor_sync(0xffffffff, d1, o);
        }
        mu0 = s0 * (1.f / DM); mu1 = s1 * (1.f / DM);
        rs0 = rsqrtf(fmaxf(q0 * (1.f / DM) - mu0 * mu0, 0.f) + 1e-5f); rs1 = rsqrtf(fmaxf(q1 * (1.f / DM) - mu1 * mu1, 0.f) + 1e-5f);
        r0 = rs0 * (d0 - mu0 * sw); r1 = rs1 * (d1 - mu1 * sw);
    }
    if (tid == 0) DBG_T(2, 7);
    uint32_t c0key, c1key;
    {
        auto mkkey = [&](float r, int rw) {
            const uint32_t b = __bfloat16_as_ushort(__float2bfloat16_rn(r));
            const uint32_t ord = (b & 0x8000u) ? (~b & 0xFFFFu) : (b | 0x8000u);
            return (ord << 16) | (uint32_t)(S_LEN - 1 - rw);
        };
        const uint32_t ka = mkkey(r0, row), kb = mkkey(r1, row + 8);
        const uint32_t k1 = max(ka, kb), k2 = min(ka, kb);
        const uint32_t t1 = __reduce_max_sync(0xffffffff, k1);
        const uint32_t t2 = __reduce_max_sync(0xffffffff, k1 == t1 ? k2 : k1);
        if (lane == 0) sts64(sb + P3_KEYS + 8 * warp, t1, t2);
        bar_sync(5, 256);
        const uint32_t k = lds32(sb + P3_KEYS + 4 * (lane & 15));
        c0key = __reduce_max_sync(0xffffffff, k);
        c1key = __reduce_max_sync(0xffffffff, k == c0key ? 0u : k);
    }
    if (tid < 2) st_ll(g_ll_key + 256 * (j & 3) + 16 * mt + tid, tid ? c1key : c0key, tag);
    #pragma unroll
    for (int c = 0; c < 2; c++) {
        const int cr = S_LEN - 1 - (int)((c ? c1key : c0key) & 0xFFFFu);
        if (cr == row || cr == row + 8) {
            const bool hi = cr != row;
            uint64_t* p = g_ll_row + (2 * mt + c) * 320 + 40 * j + t;
            #pragma unroll
            for (int b = 0; b < 10; b++) st_ll(p + 4 * b, hi ? hp[2 * b + 1] : hp[2 * b], tag);
            if (t == 0) st_ll4(g_ll_sc + 8 * (2 * mt + c), __float_as_uint(hi ? mu1 : mu0), __float_as_uint(hi ? rs1 : rs0), __float_as_uint(hi ? r1 : r0), tag);
        }
    }
    if (tid == 0) DBG_T(2, 8);
    #pragma unroll
    for (int b = 0; b < 10; b++) {
        hp[2 * b] = add_bf16x2(hp[2 * b], pack_bf16((bf_lo(hp[2 * b]) - mu0) * rs0, (bf_hi(hp[2 * b]) - mu0) * rs0));
        hp[2 * b + 1] = add_bf16x2(hp[2 * b + 1], pack_bf16((bf_lo(hp[2 * b + 1]) - mu1) * rs1, (bf_hi(hp[2 * b + 1]) - mu1) * rs1));
    }
    if (warp == 0) {
        uint64_t v; uint32_t n = 0;
        while (true) {
            v = ld_ll1(g_ll_key + 256 * (j & 3) + 16 * (lane >> 1) + (lane & 1));
            if (__all_sync(0xffffffff, (uint32_t)(v >> 32) == tag)) break;
            if (++n > SPIN_LIM) break;
        }
        const uint32_t k = (uint32_t)v;
        const uint32_t t1 = __reduce_max_sync(0xffffffff, k);
        const uint32_t t2 = __reduce_max_sync(0xffffffff, k == t1 ? 0u : k);
        const uint32_t sl0 = __ffs(__ballot_sync(0xffffffff, k == t1)) - 1, sl1 = __ffs(__ballot_sync(0xffffffff, k == t2)) - 1;
        if (lane == 0) { sts64(sb + P3_KEYS + 64, t1, t2); sts64(sb + P3_KEYS + 72, sl0, sl1); if (cta == 0) g_epoch = tag; }
    }
    bar_sync(5, 256);
    int slot0, slot1, idx0, idx1;
    {
        const uint4 v = lds128(sb + P3_KEYS + 64);
        idx0 = S_LEN - 1 - (int)(v.x & 0xFFFFu); idx1 = S_LEN - 1 - (int)(v.y & 0xFFFFu); slot0 = v.z; slot1 = v.w;
    }
    if (tid == 0) DBG_T(2, 9);
    const bool ffn = cta < 96, fin = cta >= 96 && cta < 124;
    uint64_t ra0, ra1, rb0, rb1, fh = 0;
    uint4 sa, sc;
    const int unit = 2 * (cta - 96) + wg, w2 = unit / 7, pk = unit % 7;
    int frow = 0, fcol = 0; bool fvalid = false;
    if (fin && wq == 0) {
        const int l2 = lane / 3, e = 3 * pk + lane % 3;
        frow = (l2 >> 2) & 1; fcol = 80 * w2 + 16 * (e >> 2) + ((e >> 1) & 1) * 8 + 2 * (l2 & 3) + (e & 1);
        fvalid = lane < 24 && e < 20;
    }
    const uint64_t* pa = g_ll_row + slot0 * 320 + 2 * tid; const uint64_t* pb = g_ll_row + slot1 * 320 + 2 * tid;
    const uint64_t* pfh = g_ll_row + (frow ? slot1 : slot0) * 320 + (fcol >> 1);
    const bool ld1 = ffn && tid < 160, ld2 = fvalid;
    auto fetch = [&]() {
        if (ld1) { ld_ll2(ra0, ra1, pa); ld_ll2(rb0, rb1, pb); }
        if (ld1 || ld2) { sa = ld_ll4(g_ll_sc + 8 * slot0); sc = ld_ll4(g_ll_sc + 8 * slot1); }
        if (ld2) fh = ld_ll1(pfh);
    };
    {
        uint32_t n = 0;
        while (true) {
            fetch();
            bool ok = true;
            if (ld1) ok = (uint32_t)(ra0 >> 32) == tag && (uint32_t)(ra1 >> 32) == tag && (uint32_t)(rb0 >> 32) == tag && (uint32_t)(rb1 >> 32) == tag;
            if (ld1 || ld2) ok = ok && sa.w == tag && sc.w == tag;
            if (ld2) ok = ok && (uint32_t)(fh >> 32) == tag;
            if (ok) break;
            if (++n > SPIN_LIM) break;
        }
    }
    if (tid == 0) DBG_T(3, 4);
    if (ffn) {
        if (ld1) {
            const float ma = __uint_as_float(sa.x), ia = __uint_as_float(sa.y), mb = __uint_as_float(sc.x), ib = __uint_as_float(sc.y);
            sts64(sb + P3_XS + 8 * tid, pack_bf16((bf_lo((uint32_t)ra0) - ma) * ia, (bf_hi((uint32_t)ra0) - ma) * ia), pack_bf16((bf_lo((uint32_t)ra1) - ma) * ia, (bf_hi((uint32_t)ra1) - ma) * ia));
            sts64(sb + P3_XS + 1280 + 8 * tid, pack_bf16((bf_lo((uint32_t)rb0) - mb) * ib, (bf_hi((uint32_t)rb0) - mb) * ib), pack_bf16((bf_lo((uint32_t)rb1) - mb) * ib, (bf_hi((uint32_t)rb1) - mb) * ib));
        }
        mbar_wait(bar_w1, 0);
        bar_sync(5, 256);
        if (tid == 0) DBG_T(3, 5);
        float ag[2][4] = {}, au[2][4] = {};
        #pragma unroll
        for (int ks = 0; ks < 5; ks++) {
            const int k0 = 16 * (5 * warp + ks);
            uint32_t a0 = 0, a2 = 0;
            if (g < 2) { a0 = lds32(sb + P3_XS + g * 1280 + (k0 + 2 * t) * 2); a2 = lds32(sb + P3_XS + g * 1280 + (k0 + 8 + 2 * t) * 2); }
            const uint32_t off = (k0 + (lane & 7) + ((lane >> 3) & 1) * 8) * 32 + (lane >> 4) * 16;
            uint32_t b0, b1, b2, b3;
            ldsm_x4_t(b0, b1, b2, b3, sb + P3_WG + off);
            mma16816(ag[0], a0, a2, b0, b1); mma16816(ag[1], a0, a2, b2, b3);
            ldsm_x4_t(b0, b1, b2, b3, sb + P3_WU + off);
            mma16816(au[0], a0, a2, b0, b1); mma16816(au[1], a0, a2, b2, b3);
        }
        if (g < 2) {
            const uint32_t p = sb + P3_RED + 4 * (warp * 64 + g * 32 + 2 * t);
            stsf(p, ag[0][0]); stsf(p + 4, ag[0][1]); stsf(p + 32, ag[1][0]); stsf(p + 36, ag[1][1]);
            stsf(p + 64, au[0][0]); stsf(p + 68, au[0][1]); stsf(p + 96, au[1][0]); stsf(p + 100, au[1][1]);
        }
        bar_sync(5, 256);
        if (tid == 0) DBG_T(3, 6);
        if (warp == 0) {
            const int rsel = lane >> 4, f = lane & 15;
            float gs = 0.f, us = 0.f;
            #pragma unroll
            for (int w = 0; w < 8; w++) { gs += ldsf(sb + P3_RED + 4 * (w * 64 + rsel * 32 + f)); us += ldsf(sb + P3_RED + 4 * (w * 64 + rsel * 32 + 16 + f)); }
            gs = bf_round(gs); us = bf_round(us);
            const float si = bf_round(gs / (1.f + __expf(-gs)));
            asm volatile("st.shared.b16 [%0], %1;" :: "r"(sb + P3_ACT + 2 * lane), "h"(__bfloat16_as_ushort(__float2bfloat16_rn(si * us))) : "memory");
        }
        if (tid == 0) DBG_T(3, 7);
        mbar_wait(bar_w2, 0);
        bar_sync(5, 256);
        if (tid == 0) DBG_T(3, 8);
        uint32_t a0 = 0, a2 = 0;
        if (g < 2) { a0 = lds32(sb + P3_ACT + g * 32 + 4 * t); a2 = lds32(sb + P3_ACT + g * 32 + 16 + 4 * t); }
        float yv[21];
        yv[20] = 0.f;
        #pragma unroll
        for (int i = 0; i < 5; i++) {
            const uint32_t ad = sb + P3_WD + ((lane & 7) + ((lane >> 3) & 1) * 8) * 1296 + (80 * warp + 16 * i + (lane >> 4) * 8) * 2;
            uint32_t b0, b1, b2, b3;
            ldsm_x4_t(b0, b1, b2, b3, ad);
            float y0[4] = {}, y1[4] = {};
            mma16816(y0, a0, a2, b0, b1); mma16816(y1, a0, a2, b2, b3);
            yv[4 * i] = y0[0]; yv[4 * i + 1] = y0[1]; yv[4 * i + 2] = y1[0]; yv[4 * i + 3] = y1[1];
        }
        if (g < 2) {
            uint4* p = g_ll_y + (size_t)(cta * 8 + warp) * 56 + lane;
            #pragma unroll
            for (int k = 0; k < 7; k++) st_ll4(p + k * 8, __float_as_uint(yv[3 * k]), __float_as_uint(yv[3 * k + 1]), __float_as_uint(yv[3 * k + 2]), tag);
        }
    }
    if (tid == 0) DBG_T(2, 12);
    {
        const uint32_t st = sb + P3_OST + warp * 2816;
        #pragma unroll
        for (int b = 0; b < 10; b++) { sts32(st + g * 176 + 16 * b + 4 * t, hp[2 * b]); sts32(st + (g + 8) * 176 + 16 * b + 4 * t, hp[2 * b + 1]); }
        __syncwarp();
        const int wrow = row - g;
        #pragma unroll
        for (int i = 0; i < 5; i++) {
            const int q = lane + 32 * i, r = q / 10, c = q % 10;
            const uint4 v = lds128(st + r * 176 + c * 16);
            if (wrow + r != idx0 && wrow + r != idx1) *(uint4*)(out + (size_t)(wrow + r) * DM + 80 * j + 8 * c) = v;
        }
    }
    if (tid == 0) DBG_T(2, 13);
    if (fin) {
        const uint4* p = g_ll_y + (size_t)((24 * wq + (lane >> 3)) * 8 + w2) * 56 + pk * 8 + (lane & 7);
        uint4 v[6]; uint32_t n = 0;
        while (true) {
            bool ok = true;
            #pragma unroll
            for (int k = 0; k < 6; k++) v[k] = ld_ll4(p + 4 * 8 * 56 * k);
            #pragma unroll
            for (int k = 0; k < 6; k++) ok = ok && v[k].w == tag;
            if (__all_sync(0xffffffff, ok)) break;
            if (++n > SPIN_LIM) break;
        }
        float y0 = 0.f, y1 = 0.f, y2 = 0.f;
        #pragma unroll
        for (int k = 0; k < 6; k++) { y0 += __uint_as_float(v[k].x); y1 += __uint_as_float(v[k].y); y2 += __uint_as_float(v[k].z); }
        #pragma unroll
        for (int o = 8; o <= 16; o <<= 1) { y0 += __shfl_xor_sync(0xffffffff, y0, o); y1 += __shfl_xor_sync(0xffffffff, y1, o); y2 += __shfl_xor_sync(0xffffffff, y2, o); }
        if (lane < 8) { const uint32_t a = sb + P3_RED + (warp * 8 + lane) * 16; stsf(a, y0); stsf(a + 4, y1); stsf(a + 8, y2); }
        bar_sync(1 + wg, 128);
        if (fvalid) {
            const uint32_t a = sb + P3_RED + (warp * 8 + lane / 3) * 16 + (lane % 3) * 4;
            const float s = (ldsf(a) + ldsf(a + 128)) + (ldsf(a + 256) + ldsf(a + 384));
            const float mu = __uint_as_float(frow ? sc.x : sa.x), rs = __uint_as_float(frow ? sc.y : sa.y), rr = __uint_as_float(frow ? sc.z : sa.z);
            const float sg = bf_round(1.f / (1.f + __expf(-bf_round(rr))));
            const float h = (fcol & 1) ? bf_hi((uint32_t)fh) : bf_lo((uint32_t)fh);
            const float z = bf_round(bf_round((h - mu) * rs) + bf_round(bf_round(s) * sg));
            out[(size_t)(frow ? idx1 : idx0) * DM + fcol] = __float2bfloat16_rn(h + z);
        }
    }
    if (tid == 0) DBG_T(2, 14);
}

__device__ __forceinline__ void helper_cta(const uint32_t sb, const int tid, const int warp, const int lane, const int c, const uint32_t tag,
                                           const bf16* __restrict__ wo, const bf16* __restrict__ wg_, const bf16* __restrict__ wu_, const bf16* __restrict__ wd_) {
    const uint32_t hb = sb + SM_MISC;
    if (tid == 0) {
        for (int i = 0; i < 3; i++) mbar_init(hb + 8 * i, 1);
        fence_mbar_init();
        DBG_T(3, 0);
        mbar_expect_tx(hb, 160 * 1280);
    }
    __syncthreads();
    if (tid < 160) bulk_g2s(sb + tid * 1296, wo + (size_t)(160 * c + tid) * DM, 1280, hb);
    mbar_wait(hb, 0);
    #pragma unroll 4
    for (int i = warp; i < 400; i += 16) {
        const int kg = i / 20, nc = (i % 20) * 4 + (lane >> 3);
        const int kp = 8 * kg + (lane & 7), st = kp / 80, r = kp % 80;
        const int row = 80 * st + (r < 64 ? (r >> 4) * 20 + (r & 15) : ((r - 64) >> 2) * 20 + 16 + (r & 3));
        const uint4 v = lds128(sb + row * 1296 + nc * 16);
        *(uint4*)(g_wo + (nc / 10) * 102400 + (20 * c + kg) * 1280 + (nc % 10) * 128 + (lane & 7) * 16) = v;
    }
    fence_proxy_async_global();
    __syncthreads();
    if (tid == 0) { red_release(g_cnt + 32 * 8, 1); DBG_T(3, 1); }
    if (tid >= 160 && tid < 190) {
        const char* src = (const char*)wd_ + (c * 30 + tid - 160) * 16384;
        asm volatile("cp.async.bulk.prefetch.L2.global [%0], %1;" :: "l"(src), "r"(16384) : "memory");
    }
    auto fetch = [&](int bt) {
        const uint32_t buf = sb + (bt & 1) * (32 * 3104), bar = hb + 8 + 8 * (bt & 1);
        if (tid == 0) mbar_expect_tx(bar, 32 * 3072);
        __syncwarp();
        if (tid < 32) bulk_g2s(buf + tid * 3104, (const char*)(tid < 16 ? wg_ : wu_) + (size_t)(160 * c + 16 * bt + (tid & 15)) * 3072, 3072, bar);
    };
    if (warp == 0) { fetch(0); fetch(1); }
    #pragma unroll 1
    for (int bt = 0; bt < 10; bt++) {
        const uint32_t buf = sb + (bt & 1) * (32 * 3104);
        mbar_wait(hb + 8 + 8 * (bt & 1), (bt >> 1) & 1);
        #pragma unroll
        for (int i = 0; i < 12; i++) {
            const int pc = warp * 12 + i, sl = pc >> 1, m = pc & 1;
            const uint4 v = lds128(buf + (m * 16 + (lane >> 1)) * 3104 + sl * 32 + (lane & 1) * 16);
            *(uint4*)(g_wgu + (size_t)sl * 40960 + m * 20480 + (160 * c + 16 * bt) * 32 + lane * 16) = v;
        }
        __syncthreads();
        if (warp == 0 && bt + 2 < 10) fetch(bt + 2);
    }
    fence_proxy_async_global();
    __syncthreads();
    if (tid == 0) { red_release(g_cnt + 32 * 9, 1); DBG_T(3, 2); }
}

typedef CUresult (*EncodeFn)(CUtensorMap*, CUtensorMapDataType, cuuint32_t, void*, const cuuint64_t*, const cuuint64_t*, const cuuint32_t*, const cuuint32_t*,
                             CUtensorMapInterleave, CUtensorMapSwizzle, CUtensorMapL2promotion, CUtensorMapFloatOOBfill);

#define PROM_X CU_TENSOR_MAP_L2_PROMOTION_L2_128B
#define PROM_W CU_TENSOR_MAP_L2_PROMOTION_L2_128B
static void make_map(EncodeFn enc, CUtensorMap* tm, const void* ptr, uint64_t inner, uint64_t outer, uint32_t box_in, uint32_t box_out, CUtensorMapL2promotion prom) {
    cuuint64_t dims[2] = {inner, outer};
    cuuint64_t strides[1] = {inner * 2};
    cuuint32_t box[2] = {box_in, box_out};
    cuuint32_t es[2] = {1, 1};
    enc(tm, CU_TENSOR_MAP_DATA_TYPE_BFLOAT16, 2, const_cast<void*>(ptr), dims, strides, box, es, CU_TENSOR_MAP_INTERLEAVE_NONE,
        CU_TENSOR_MAP_SWIZZLE_128B, prom,
        CU_TENSOR_MAP_FLOAT_OOB_FILL_NONE);
}

__global__ void __launch_bounds__(NTHREADS, 1)
fused_block(const __grid_constant__ CUtensorMap tmX, const __grid_constant__ CUtensorMap tmW, const bf16* __restrict__ x, const bf16* __restrict__ wqkv, const bf16* __restrict__ wo,
            const bf16* __restrict__ wr, const bf16* __restrict__ wgate, const bf16* __restrict__ wup, const bf16* __restrict__ wdown, bf16* __restrict__ out) {
    extern __shared__ uint8_t smem_raw[];
    const uint32_t sb = (smem_u32(smem_raw) + 1023) & ~1023u;
    const int tid = threadIdx.x;
    const int warp = __shfl_sync(0xffffffff, tid >> 5, 0), lane = tid & 31;
    const int wgi = __shfl_sync(0xffffffff, tid >> 7, 0);
    const int b = blockIdx.x;
    const int mt = 2 * (b >> 4) + (b & 1), j = (b & 15) >> 1;
    if (b >= 128) {
        helper_cta(sb, tid, warp, lane, b - 128, ld_relaxed(&g_epoch) + 1, wo, wgate, wup, wdown);
        return;
    }
    if (warp == 0) {
        if (lane == 0) {
            DBG_T(0, 0);
            for (int i = 0; i < 4; i++) mbar_init(sb + B1_FULL + 8 * i, 1);
            fence_mbar_init();
        }
        __syncwarp();
        #pragma unroll
        for (int it = 0; it < P1_PRE; it++) p1_issue(sb, &tmX, &tmW, mt, j, it);
    } else if (tid == 32) {
        for (int i = 0; i < 4; i++) mbar_init(sb + B1_EMPTY + 8 * i, 2);
        mbar_init(sb + B1_GO, 2); mbar_init(sb + B1_FREE, 2); mbar_init(sb + B1_READY, 128); mbar_init(sb + B1_END, 12);
        for (int i = 0; i < 3; i++) mbar_init(sb + B1_STAGED + 8 * i, 8);
        p2_init(sb);
        for (int i = 0; i < 16; i++) mbar_init(sb + B3_FULL + 8 * i, 1);
        for (int i = 0; i < 8; i++) mbar_init(sb + B3_EMPTY + 8 * i, 4);
        mbar_init(sb + B3_B, 1); mbar_init(sb + B3_W1, 1); mbar_init(sb + B3_W2, 1);
        fence_mbar_init();
    }
    const uint32_t tag = ld_relaxed(&g_epoch) + 1;
    __syncthreads();
    p1_phase(sb, tid, warp, lane, wgi, b, mt, j, tag, &tmX, &tmW, wqkv);
    p2_phase(sb, tid, warp, lane, b);
    p3_phase(sb, tid, warp, lane, b, x, wr, wdown, out);
}

extern "C" void kernel_launch(void* const* d_in, const int* in_sizes, int n_in, void* d_out, int out_size) {
    const bf16* x = (const bf16*)d_in[0];
    const bf16* wqkv = (const bf16*)d_in[1];
    const bf16* wo = (const bf16*)d_in[2];
    const bf16* wr = (const bf16*)d_in[4];
    const bf16* wgate = (const bf16*)d_in[5];
    const bf16* wup = (const bf16*)d_in[6];
    const bf16* wdown = (const bf16*)d_in[7];
    static bool init = false;
    static EncodeFn enc = nullptr;
    if (!init) {
        void* fn = nullptr; cudaDriverEntryPointQueryResult qr;
        cudaGetDriverEntryPoint("cuTensorMapEncodeTiled", &fn, cudaEnableDefault, &qr);
        enc = (EncodeFn)fn;
        cudaFuncSetAttribute(fused_block, cudaFuncAttributeMaxDynamicSharedMemorySize, SM_TOTAL);
        init = true;
    }
    CUtensorMap tmX, tmW;
    make_map(enc, &tmX, x, DM, S_LEN, 64, 128, PROM_X);
    make_map(enc, &tmW, wqkv, 3 * DM, DM, 64, 64, PROM_W);
    fused_block<<<132, NTHREADS, SM_TOTAL, cudaStreamPerThread>>>(tmX, tmW, x, wqkv, wo, wr, wgate, wup, wdown, (bf16*)d_out);
}
```
